```python
import torch

def _softmax(x, axis=-1):
    return torch.softmax(x, dim=axis)
def _gelu(x):
    return torch.nn.functional.gelu(x, approximate="tanh")
def _silu(x):
    return torch.nn.functional.silu(x)
def _sigmoid(x):
    return torch.sigmoid(x)
def _layernorm(x, axis=-1, eps=1e-5):
    m = x.mean(dim=axis, keepdim=True)
    v = x.var(dim=axis, keepdim=True, unbiased=False)
    return (x - m) / torch.sqrt(v + eps)
def _scatter_add(tgt, idx, src, axis=0):
    return tgt.clone().index_add_(axis, idx, src)
def _segment_sum(src, seg, n):
    out = torch.zeros((n,) + src.shape[1:], dtype=src.dtype)
    return out.index_add_(0, seg, src)
def _pad(x, pw):
    flat = tuple(v for pair in reversed(pw) for v in pair)
    return torch.nn.functional.pad(x, flat)

kernel_name = 'gated_mix__sliding_block__dense_activation_relu__prompt'

def setup_inputs():

    _w = (lambda a: (lambda t: t.to(torch.bfloat16) if t.is_floating_point() else t)(torch.as_tensor(a)))
    def _A_setup():
        B, S, D = 1, 2048, 512
        return {
            "x": _w((lambda *s: torch.randn(*s, dtype=torch.bfloat16) * 0.05)(B, S, D)),
            "wqkv": _w((lambda *s: torch.randn(*s, dtype=torch.bfloat16) * 0.8)(D, 3 * D)),
            "wo": _w((lambda *s: torch.randn(*s, dtype=torch.bfloat16) * 0.05)(D, D)),
        }
    _A_in = _A_setup()

    def _B_setup():
        B, S, D, Dff = 1, 2048, 512, 1376
        return {
            "x": _w((lambda *s: torch.randn(*s, dtype=torch.bfloat16) * 0.05)(B, S, D)),
            "w1": _w((lambda *s: torch.randn(*s, dtype=torch.bfloat16) * 0.05)(D, Dff)),
            "w2": _w((lambda *s: torch.randn(*s, dtype=torch.bfloat16) * 0.05)(Dff, D)),
        }
    _B_in = _B_setup()

    return {
        "A_x": _A_in["x"],
        "A_wqkv": _A_in["wqkv"],
        "A_wo": _A_in["wo"],
        "B_x": _B_in["x"],
        "B_w1": _B_in["w1"],
        "B_w2": _B_in["w2"],
        "gate_w": _w((lambda *s: torch.randn(*s, dtype=torch.bfloat16) * 0.05)(512) * 16.0),
    }

def reference(A_x, A_wqkv, A_wo, B_x, B_w1, B_w2, gate_w):
    def _A_ref(x, wqkv, wo):
        B, S, D = x.shape
        H = 32; Dh = D // H; W = 256
        qkv = (lambda x, *d: x.permute(*d))((x @ wqkv).reshape(B, S, 3, H, Dh), 2, 0, 3, 1, 4)
        q, k, v = qkv[0], qkv[1], qkv[2]
        scores = torch.einsum("bhqd,bhkd->bhqk", q, k) * (Dh ** -0.5)
        idx = torch.arange(S)
        mask = (idx[:, None] - idx[None, :] >= 0) & (idx[:, None] - idx[None, :] < W)
        scores = torch.where(mask[None, None], scores, -1e9)
        p = _softmax(scores, axis=-1)
        o = torch.einsum("bhqk,bhkd->bhqd", p, v)
        return (lambda x, *d: x.permute(*d))(o, 0, 2, 1, 3).reshape(B, S, D) @ wo

    def _B_ref(x, w1, w2):
        h = torch.einsum("bsd,df->bsf", x, w1)
        zero = torch.zeros_like(h)
        h = torch.maximum(h, zero)
        return torch.einsum("bsf,fd->bsd", h, w2)

    x = A_x
    g = _sigmoid((x * gate_w).sum(-1, keepdims=True))
    a = _A_ref(x, A_wqkv, A_wo)
    b = _B_ref(x, B_w1, B_w2)
    return g * a + (1 - g) * b
```

```cpp
#include <cuda_runtime.h>
#include <cuda_bf16.h>
#include <cuda.h>
#include <stdint.h>

namespace {

constexpr int S_ = 2048, D_ = 512, DFF = 1376;
constexpr int A2_BYTES = 236 * 2048;
constexpr float QSCALE = 0.25f * 1.4426950408889634f;

constexpr uint32_t SM_X = 0;
constexpr uint32_t SM_U = 131072;
constexpr uint32_t SM_L = SM_U;
constexpr uint32_t SM_V = SM_U + 32768;
constexpr uint32_t SM_T = SM_V + 40960;
constexpr uint32_t SM_BAR = 229376;
constexpr uint32_t SM_G = SM_BAR + 1280;
constexpr uint32_t SM_GW = SM_G + 512;
constexpr uint32_t SM_TOTAL = SM_GW + 1024;
static_assert(SM_TOTAL <= 232448, "smem");

enum : int {
  B_KVFULL = 0,
  B_QFULL = 8,
  B_W1FULL = 16,
  B_G2FULL = 32,
  B_HALO = 62,
  B_GWFULL = 66,
  B_AKV = 67,
  B_AQ = 75,
  B_F1 = 83,
  B_F2 = 99,
  B_HEAD = 129,
  B_KVW = 133,
  B_HW = 134,
  B_HFREE = 136,
  B_GRDY = 138,
  B_COUNT = 139
};

struct Maps { CUtensorMap x, wkv, wq, w1a, w1s, w2, wo, out; };

__device__ uint4 g_kv[128 * 2048];
__device__ uint4 g_a2[16 * (A2_BYTES / 16)];
__device__ uint4 g_zero[512];
__device__ unsigned g_kvflag[128 * 32];
__device__ unsigned g_cnt[16 * 8 * 32];
__device__ unsigned g_epoch[128];
#define TR(i)

__device__ __forceinline__ bool elect() {
  uint32_t p;
  asm volatile("{.reg .pred p; elect.sync _|p, 0xffffffff; selp.u32 %0, 1, 0, p;}" : "=r"(p));
  return p;
}
__device__ __forceinline__ void mbar_wait(uint32_t bar) {
  asm volatile("{.reg .pred p; .reg .b32 c; .reg .b64 z;\n"
               "mbarrier.try_wait.parity.shared::cta.b64 p, [%0], 0;\n @p bra DONE_%=;\n mov.b32 c, 0;\n"
               "LOOP_%=: mbarrier.try_wait.parity.shared::cta.b64 p, [%0], 0;\n @p bra DONE_%=;\n"
               "add.u32 c, c, 1; setp.gt.u32 p, c, 2000000; mov.b64 z, 0; @p st.global.u32 [z], c;\n bra LOOP_%=;\n"
               "DONE_%=: }" ::"r"(bar) : "memory");
}
__device__ __forceinline__ void mbar_arrive(uint32_t bar) {
  asm volatile("mbarrier.arrive.shared::cta.b64 _, [%0];" ::"r"(bar) : "memory");
}
__device__ __forceinline__ void warp_arrive(uint32_t bar) {
  __syncwarp();
  if (elect()) mbar_arrive(bar);
}
__device__ __forceinline__ void mbar_expect(uint32_t bar, uint32_t bytes) {
  asm volatile("mbarrier.arrive.expect_tx.shared::cta.b64 _, [%0], %1;" ::"r"(bar), "r"(bytes) : "memory");
}
__device__ __forceinline__ void tma2d(uint32_t dst, const CUtensorMap* m, int c0, int c1, uint32_t bar) {
  asm volatile("cp.async.bulk.tensor.2d.shared::cluster.global.mbarrier::complete_tx::bytes [%0], [%1, {%3, %4}], [%2];"
               ::"r"(dst), "l"(m), "r"(bar), "r"(c0), "r"(c1) : "memory");
}
__device__ __forceinline__ void tma3d(uint32_t dst, const CUtensorMap* m, int c0, int c1, int c2, uint32_t bar) {
  asm volatile("cp.async.bulk.tensor.3d.shared::cluster.global.mbarrier::complete_tx::bytes [%0], [%1, {%3, %4, %5}], [%2];"
               ::"r"(dst), "l"(m), "r"(bar), "r"(c0), "r"(c1), "r"(c2) : "memory");
}
__device__ __forceinline__ void bulk_load(uint32_t dst, const void* src, uint32_t bytes, uint32_t bar) {
  asm volatile("cp.async.bulk.shared::cluster.global.mbarrier::complete_tx::bytes [%0], [%1], %2, [%3];"
               ::"r"(dst), "l"(src), "r"(bytes), "r"(bar) : "memory");
}
__device__ __forceinline__ void bulk_store(void* dst, uint32_t src, uint32_t bytes) {
  asm volatile("cp.async.bulk.global.shared::cta.bulk_group [%0], [%1], %2;" ::"l"(dst), "r"(src), "r"(bytes) : "memory");
}
__device__ __forceinline__ void bulk_commit_wait() {
  asm volatile("cp.async.bulk.commit_group;\n cp.async.bulk.wait_group 0;" ::: "memory");
}
__device__ __forceinline__ void l2_prefetch(const void* p, uint32_t bytes) {
  asm volatile("cp.async.bulk.prefetch.L2.global [%0], %1;" ::"l"(p), "r"(bytes) : "memory");
}
__device__ __forceinline__ void fence_async_smem() { asm volatile("fence.proxy.async.shared::cta;" ::: "memory"); }
__device__ __forceinline__ void fence_async_all() { asm volatile("fence.proxy.async;" ::: "memory"); }
__device__ __forceinline__ void flag_wait(const unsigned* f, unsigned target) {
  unsigned v, it = 0;
  do {
    asm volatile("ld.acquire.gpu.global.u32 %0, [%1];" : "=r"(v) : "l"(f) : "memory");
    if (++it > (1u << 22)) asm volatile("st.global.u32 [%0], %1;" ::"l"(0ull), "r"(it) : "memory");
  } while ((int)(v - target) < 0);
  fence_async_all();
}
__device__ __forceinline__ void flag_add(unsigned* f) {
  fence_async_all();
  asm volatile("red.release.gpu.global.add.u32 [%0], 1;" ::"l"(f) : "memory");
}
__device__ __forceinline__ void stsm4(uint32_t addr, uint32_t a, uint32_t b, uint32_t c, uint32_t d) {
  asm volatile("stmatrix.sync.aligned.m8n8.x4.shared.b16 [%0], {%1, %2, %3, %4};" ::"r"(addr), "r"(a), "r"(b), "r"(c), "r"(d) : "memory");
}
__device__ __forceinline__ uint32_t pack(float lo, float hi) {
  uint32_t r; asm("cvt.rn.bf16x2.f32 %0, %1, %2;" : "=r"(r) : "f"(hi), "f"(lo)); return r;
}
__device__ __forceinline__ uint32_t pack_relu(float lo, float hi) {
  uint32_t r; asm("cvt.rn.relu.bf16x2.f32 %0, %1, %2;" : "=r"(r) : "f"(hi), "f"(lo)); return r;
}
__device__ __forceinline__ float ex2(float x) { float y; asm("ex2.approx.ftz.f32 %0, %1;" : "=f"(y) : "f"(x)); return y; }
__device__ __forceinline__ float lds_f32(uint32_t a) { float v; asm volatile("ld.shared.f32 %0, [%1];" : "=f"(v) : "r"(a) : "memory"); return v; }
__device__ __forceinline__ uint4 lds_v4(uint32_t a) {
  uint4 v; asm volatile("ld.shared.v4.u32 {%0,%1,%2,%3}, [%4];" : "=r"(v.x), "=r"(v.y), "=r"(v.z), "=r"(v.w) : "r"(a) : "memory"); return v;
}
#define WG_FENCE() asm volatile("wgmma.fence.sync.aligned;" ::: "memory")
#define WG_COMMIT() asm volatile("wgmma.commit_group.sync.aligned;" ::: "memory")
#define WG_WAIT(n) asm volatile("wgmma.wait_group.sync.aligned " #n ";" ::: "memory")
#define SCHED_BAR() asm volatile("pmevent 1;" ::: "memory")
template <int N> __device__ __forceinline__ void pin(float (&d)[N]) {
#pragma unroll
  for (int i = 0; i < N; i++) asm volatile("" : "+f"(d[i])::"memory");
}
template <int N> __device__ __forceinline__ void pin(uint32_t (&d)[N]) {
#pragma unroll
  for (int i = 0; i < N; i++) asm volatile("" : "+r"(d[i])::"memory");
}

constexpr uint32_t HI_SW128 = (1024 >> 4) | (1u << 30);
constexpr uint32_t HI_SW64 = (512 >> 4) | (2u << 30);
constexpr uint32_t HI_A2 = (128 >> 4);
constexpr int LO_X = 1 << 16, LO_W128 = (8192 >> 4) << 16, LO_W64 = (4096 >> 4) << 16, LO_A2 = (2048 >> 4) << 16;

template <int AOFF, uint32_t AHI, int BOFF, uint32_t BHI>
__device__ __forceinline__ void wgmma_ss(float (&d)[32], uint32_t alo, uint32_t blo, int acc) {
  asm volatile("{.reg .pred p; .reg .b32 ta, tb; .reg .b64 da, db; setp.ne.b32 p, %34, 0;\n"
    "add.u32 ta, %32, %35; mov.b64 da, {ta, %36}; add.u32 tb, %33, %37; mov.b64 db, {tb, %38};\n"
    "wgmma.mma_async.sync.aligned.m64n64k16.f32.bf16.bf16 {%0,%1,%2,%3,%4,%5,%6,%7,%8,%9,%10,%11,%12,%13,%14,%15,%16,%17,%18,%19,%20,%21,%22,%23,%24,%25,%26,%27,%28,%29,%30,%31}, da, db, p, 1, 1, 0, 1;}"
    : "+f"(d[0]),"+f"(d[1]),"+f"(d[2]),"+f"(d[3]),"+f"(d[4]),"+f"(d[5]),"+f"(d[6]),"+f"(d[7]),"+f"(d[8]),"+f"(d[9]),"+f"(d[10]),"+f"(d[11]),"+f"(d[12]),"+f"(d[13]),"+f"(d[14]),"+f"(d[15]),"+f"(d[16]),"+f"(d[17]),"+f"(d[18]),"+f"(d[19]),"+f"(d[20]),"+f"(d[21]),"+f"(d[22]),"+f"(d[23]),"+f"(d[24]),"+f"(d[25]),"+f"(d[26]),"+f"(d[27]),"+f"(d[28]),"+f"(d[29]),"+f"(d[30]),"+f"(d[31])
    : "r"(alo), "r"(blo), "r"(acc), "n"(AOFF), "n"(AHI), "n"(BOFF), "n"(BHI));
}
template <int AOFF, uint32_t AHI, int BOFF, uint32_t BHI>
__device__ __forceinline__ void wgmma_ss(float (&d)[40], uint32_t alo, uint32_t blo, int acc) {
  asm volatile("{.reg .pred p; .reg .b32 ta, tb; .reg .b64 da, db; setp.ne.b32 p, %42, 0;\n"
    "add.u32 ta, %40, %43; mov.b64 da, {ta, %44}; add.u32 tb, %41, %45; mov.b64 db, {tb, %46};\n"
    "wgmma.mma_async.sync.aligned.m64n80k16.f32.bf16.bf16 {%0,%1,%2,%3,%4,%5,%6,%7,%8,%9,%10,%11,%12,%13,%14,%15,%16,%17,%18,%19,%20,%21,%22,%23,%24,%25,%26,%27,%28,%29,%30,%31,%32,%33,%34,%35,%36,%37,%38,%39}, da, db, p, 1, 1, 0, 1;}"
    : "+f"(d[0]),"+f"(d[1]),"+f"(d[2]),"+f"(d[3]),"+f"(d[4]),"+f"(d[5]),"+f"(d[6]),"+f"(d[7]),"+f"(d[8]),"+f"(d[9]),"+f"(d[10]),"+f"(d[11]),"+f"(d[12]),"+f"(d[13]),"+f"(d[14]),"+f"(d[15]),"+f"(d[16]),"+f"(d[17]),"+f"(d[18]),"+f"(d[19]),"+f"(d[20]),"+f"(d[21]),"+f"(d[22]),"+f"(d[23]),"+f"(d[24]),"+f"(d[25]),"+f"(d[26]),"+f"(d[27]),"+f"(d[28]),"+f"(d[29]),"+f"(d[30]),"+f"(d[31]),"+f"(d[32]),"+f"(d[33]),"+f"(d[34]),"+f"(d[35]),"+f"(d[36]),"+f"(d[37]),"+f"(d[38]),"+f"(d[39])
    : "r"(alo), "r"(blo), "r"(acc), "n"(AOFF), "n"(AHI), "n"(BOFF), "n"(BHI));
}
template <int AOFF, uint32_t AHI, int BOFF, uint32_t BHI>
__device__ __forceinline__ void wgmma_ss(float (&d)[48], uint32_t alo, uint32_t blo, int acc) {
  asm volatile("{.reg .pred p; .reg .b32 ta, tb; .reg .b64 da, db; setp.ne.b32 p, %50, 0;\n"
    "add.u32 ta, %48, %51; mov.b64 da, {ta, %52}; add.u32 tb, %49, %53; mov.b64 db, {tb, %54};\n"
    "wgmma.mma_async.sync.aligned.m64n96k16.f32.bf16.bf16 {%0,%1,%2,%3,%4,%5,%6,%7,%8,%9,%10,%11,%12,%13,%14,%15,%16,%17,%18,%19,%20,%21,%22,%23,%24,%25,%26,%27,%28,%29,%30,%31,%32,%33,%34,%35,%36,%37,%38,%39,%40,%41,%42,%43,%44,%45,%46,%47}, da, db, p, 1, 1, 0, 1;}"
    : "+f"(d[0]),"+f"(d[1]),"+f"(d[2]),"+f"(d[3]),"+f"(d[4]),"+f"(d[5]),"+f"(d[6]),"+f"(d[7]),"+f"(d[8]),"+f"(d[9]),"+f"(d[10]),"+f"(d[11]),"+f"(d[12]),"+f"(d[13]),"+f"(d[14]),"+f"(d[15]),"+f"(d[16]),"+f"(d[17]),"+f"(d[18]),"+f"(d[19]),"+f"(d[20]),"+f"(d[21]),"+f"(d[22]),"+f"(d[23]),"+f"(d[24]),"+f"(d[25]),"+f"(d[26]),"+f"(d[27]),"+f"(d[28]),"+f"(d[29]),"+f"(d[30]),"+f"(d[31]),"+f"(d[32]),"+f"(d[33]),"+f"(d[34]),"+f"(d[35]),"+f"(d[36]),"+f"(d[37]),"+f"(d[38]),"+f"(d[39]),"+f"(d[40]),"+f"(d[41]),"+f"(d[42]),"+f"(d[43]),"+f"(d[44]),"+f"(d[45]),"+f"(d[46]),"+f"(d[47])
    : "r"(alo), "r"(blo), "r"(acc), "n"(AOFF), "n"(AHI), "n"(BOFF), "n"(BHI));
}
template <int AOFF, uint32_t AHI, int BOFF, uint32_t BHI>
__device__ __forceinline__ void wgmma_ss(float (&d)[64], uint32_t alo, uint32_t blo, int acc) {
  asm volatile("{.reg .pred p; .reg .b32 ta, tb; .reg .b64 da, db; setp.ne.b32 p, %66, 0;\n"
    "add.u32 ta, %64, %67; mov.b64 da, {ta, %68}; add.u32 tb, %65, %69; mov.b64 db, {tb, %70};\n"
    "wgmma.mma_async.sync.aligned.m64n128k16.f32.bf16.bf16 {%0,%1,%2,%3,%4,%5,%6,%7,%8,%9,%10,%11,%12,%13,%14,%15,%16,%17,%18,%19,%20,%21,%22,%23,%24,%25,%26,%27,%28,%29,%30,%31,%32,%33,%34,%35,%36,%37,%38,%39,%40,%41,%42,%43,%44,%45,%46,%47,%48,%49,%50,%51,%52,%53,%54,%55,%56,%57,%58,%59,%60,%61,%62,%63}, da, db, p, 1, 1, 0, 1;}"
    : "+f"(d[0]),"+f"(d[1]),"+f"(d[2]),"+f"(d[3]),"+f"(d[4]),"+f"(d[5]),"+f"(d[6]),"+f"(d[7]),"+f"(d[8]),"+f"(d[9]),"+f"(d[10]),"+f"(d[11]),"+f"(d[12]),"+f"(d[13]),"+f"(d[14]),"+f"(d[15]),"+f"(d[16]),"+f"(d[17]),"+f"(d[18]),"+f"(d[19]),"+f"(d[20]),"+f"(d[21]),"+f"(d[22]),"+f"(d[23]),"+f"(d[24]),"+f"(d[25]),"+f"(d[26]),"+f"(d[27]),"+f"(d[28]),"+f"(d[29]),"+f"(d[30]),"+f"(d[31]),"+f"(d[32]),"+f"(d[33]),"+f"(d[34]),"+f"(d[35]),"+f"(d[36]),"+f"(d[37]),"+f"(d[38]),"+f"(d[39]),"+f"(d[40]),"+f"(d[41]),"+f"(d[42]),"+f"(d[43]),"+f"(d[44]),"+f"(d[45]),"+f"(d[46]),"+f"(d[47]),"+f"(d[48]),"+f"(d[49]),"+f"(d[50]),"+f"(d[51]),"+f"(d[52]),"+f"(d[53]),"+f"(d[54]),"+f"(d[55]),"+f"(d[56]),"+f"(d[57]),"+f"(d[58]),"+f"(d[59]),"+f"(d[60]),"+f"(d[61]),"+f"(d[62]),"+f"(d[63])
    : "r"(alo), "r"(blo), "r"(acc), "n"(AOFF), "n"(AHI), "n"(BOFF), "n"(BHI));
}
template <int OFF>
__device__ __forceinline__ void wgmma_qk(float (&d)[32], const uint32_t (&a)[4], uint32_t lo) {
  asm volatile("{.reg .b32 t; .reg .b64 db; add.u32 t, %36, %37; mov.b64 db, {t, 32};\n"
    "wgmma.mma_async.sync.aligned.m64n64k16.f32.bf16.bf16 {%0,%1,%2,%3,%4,%5,%6,%7,%8,%9,%10,%11,%12,%13,%14,%15,%16,%17,%18,%19,%20,%21,%22,%23,%24,%25,%26,%27,%28,%29,%30,%31}, {%32,%33,%34,%35}, db, 0, 1, 1, 0;}"
    : "=f"(d[0]),"=f"(d[1]),"=f"(d[2]),"=f"(d[3]),"=f"(d[4]),"=f"(d[5]),"=f"(d[6]),"=f"(d[7]),"=f"(d[8]),"=f"(d[9]),"=f"(d[10]),"=f"(d[11]),"=f"(d[12]),"=f"(d[13]),"=f"(d[14]),"=f"(d[15]),"=f"(d[16]),"=f"(d[17]),"=f"(d[18]),"=f"(d[19]),"=f"(d[20]),"=f"(d[21]),"=f"(d[22]),"=f"(d[23]),"=f"(d[24]),"=f"(d[25]),"=f"(d[26]),"=f"(d[27]),"=f"(d[28]),"=f"(d[29]),"=f"(d[30]),"=f"(d[31])
    : "r"(a[0]), "r"(a[1]), "r"(a[2]), "r"(a[3]), "r"(lo), "n"(OFF + (8 << 16)));
}
template <int OFF, int ACC>
__device__ __forceinline__ void wgmma_pv(float (&d)[8], uint32_t a0, uint32_t a1, uint32_t a2, uint32_t a3, uint32_t lo) {
  if (ACC)
    asm volatile("{.reg .b32 t; .reg .b64 db; add.u32 t, %12, %13; mov.b64 db, {t, 8};\n"
      "wgmma.mma_async.sync.aligned.m64n16k16.f32.bf16.bf16 {%0,%1,%2,%3,%4,%5,%6,%7}, {%8,%9,%10,%11}, db, 1, 1, 1, 1;}"
      : "+f"(d[0]), "+f"(d[1]), "+f"(d[2]), "+f"(d[3]), "+f"(d[4]), "+f"(d[5]), "+f"(d[6]), "+f"(d[7])
      : "r"(a0), "r"(a1), "r"(a2), "r"(a3), "r"(lo), "n"(OFF + 16 + (32 << 16)));
  else
    asm volatile("{.reg .b32 t; .reg .b64 db; add.u32 t, %12, %13; mov.b64 db, {t, 8};\n"
      "wgmma.mma_async.sync.aligned.m64n16k16.f32.bf16.bf16 {%0,%1,%2,%3,%4,%5,%6,%7}, {%8,%9,%10,%11}, db, 0, 1, 1, 1;}"
      : "=f"(d[0]), "=f"(d[1]), "=f"(d[2]), "=f"(d[3]), "=f"(d[4]), "=f"(d[5]), "=f"(d[6]), "=f"(d[7])
      : "r"(a0), "r"(a1), "r"(a2), "r"(a3), "r"(lo), "n"(OFF + 16 + (32 << 16)));
}
template <int OFF, int ACC>
__device__ __forceinline__ void pv_tile(float (&o)[8], const uint32_t (&p)[16], uint32_t lo) {
  wgmma_pv<OFF, ACC>(o, p[0], p[1], p[2], p[3], lo);
  wgmma_pv<OFF + 64, 1>(o, p[4], p[5], p[6], p[7], lo);
  wgmma_pv<OFF + 128, 1>(o, p[8], p[9], p[10], p[11], lo);
  wgmma_pv<OFF + 192, 1>(o, p[12], p[13], p[14], p[15], lo);
}
template <int LO, int HI>
__device__ __forceinline__ void fexp(float (&s)[32], float& l0, float& l1) {
#pragma unroll
  for (int i = LO; i < HI; i += 4) {
    s[i] = ex2(s[i]); s[i + 1] = ex2(s[i + 1]); s[i + 2] = ex2(s[i + 2]); s[i + 3] = ex2(s[i + 3]);
    l0 += s[i] + s[i + 1]; l1 += s[i + 2] + s[i + 3];
  }
}
__device__ __forceinline__ void packp(uint32_t (&p)[16], const float (&s)[32]) {
#pragma unroll
  for (int i = 0; i < 16; i++) p[i] = pack(s[2 * i], s[2 * i + 1]);
}
__device__ __forceinline__ void merge(float (&d)[32], const float (&e)[32], int r0, bool has_e) {
  if (has_e) {
#pragma unroll
    for (int i = 0; i < 32; i++) d[i] = (8 * (i >> 2) + (i & 1) <= r0 + 4 * (i & 2)) ? d[i] : e[i];
  } else {
#pragma unroll
    for (int i = 0; i < 32; i++) d[i] = (8 * (i >> 2) + (i & 1) <= r0 + 4 * (i & 2)) ? d[i] : -INFINITY;
  }
}
__device__ __forceinline__ uint32_t pmask(int c, int r) { return (c <= r ? 0xFFFFu : 0u) | (c + 1 <= r ? 0xFFFF0000u : 0u); }
__device__ __forceinline__ float quad_sum(float v) {
  v += __shfl_xor_sync(0xffffffffu, v, 1); v += __shfl_xor_sync(0xffffffffu, v, 2); return v;
}
__device__ __forceinline__ float quad_max(float v) {
  v = fmaxf(v, __shfl_xor_sync(0xffffffffu, v, 1)); v = fmaxf(v, __shfl_xor_sync(0xffffffffu, v, 2)); return v;
}

#define SPLIT 16

template <int NREG, int AK, uint32_t AHI, int AM, int BK, uint32_t BHI, int NK>
__device__ __forceinline__ void f_kblock(float (&d0)[NREG], float (&d1)[NREG], uint32_t alo, uint32_t blo, int acc, uint32_t prev_bar) {
  WG_FENCE();
  wgmma_ss<0, AHI, 0, BHI>(d0, alo, blo, acc);
  wgmma_ss<AM, AHI, 0, BHI>(d1, alo, blo, acc);
  WG_COMMIT();
  WG_WAIT(1);
  if (prev_bar) warp_arrive(prev_bar);
  wgmma_ss<AK, AHI, BK, BHI>(d0, alo, blo, 1);
  wgmma_ss<AK + AM, AHI, BK, BHI>(d1, alo, blo, 1);
  WG_COMMIT();
  if (NK > 2) {
    WG_WAIT(1);
    wgmma_ss<2 * AK, AHI, 2 * BK, BHI>(d0, alo, blo, 1);
    wgmma_ss<2 * AK + AM, AHI, 2 * BK, BHI>(d1, alo, blo, 1);
    WG_COMMIT();
    WG_WAIT(1);
    wgmma_ss<3 * AK, AHI, 3 * BK, BHI>(d0, alo, blo, 1);
    wgmma_ss<3 * AK + AM, AHI, 3 * BK, BHI>(d1, alo, blo, 1);
    WG_COMMIT();
  }
  WG_WAIT(1);
}

template <int NREG>
__device__ __forceinline__ void h_epilogue(const float (&d)[NREG], float sa, float sb, uint32_t addr) {
#pragma unroll
  for (int j = 0; j < NREG / 4; j += 2)
    stsm4(addr + j * 2048,
          pack_relu(d[4 * j] * sa, d[4 * j + 1] * sa), pack_relu(d[4 * j + 2] * sb, d[4 * j + 3] * sb),
          pack_relu(d[4 * j + 4] * sa, d[4 * j + 5] * sa), pack_relu(d[4 * j + 6] * sb, d[4 * j + 7] * sb));
}

template <int NREG, int N0>
__device__ __forceinline__ void ffn1_half(uint32_t sb, const float (&sc)[4], int lane, int wq) {
  float d0[NREG], d1[NREG];
#pragma unroll
  for (int i = 0; i < NREG; i++) { d0[i] = 0.f; d1[i] = 0.f; }
  const uint32_t bars = sb + SM_BAR;
#pragma unroll 1
  for (int t = 0; t < 8; t++) {
    const int n = N0 + t;
    const uint32_t alo = ((sb + SM_X + (N0 ? 4 + (t & 3) : t) * 16384) >> 4) + LO_X;
    const uint32_t blo = ((sb + SM_V + (n % 3) * 12288) >> 4) + LO_W64;
    mbar_wait(bars + 8 * (B_W1FULL + n));
    f_kblock<NREG, 2, HI_SW128, 512, 64, HI_SW64, 4>(d0, d1, alo, blo, t > 0, t > 0 ? bars + 8 * (B_F1 + n - 1) : 0);
  }
  WG_WAIT(0);
  pin(d0); pin(d1);
  warp_arrive(bars + 8 * (B_F1 + N0 + 7));
  TR(N0 ? 20 : 18);
  mbar_wait(bars + 8 * (N0 ? B_HFREE : B_AQ + 7));
  const uint32_t addr = sb + SM_T + (lane >> 4) * 2048 + (2 * wq + ((lane >> 3) & 1)) * 128 + (lane & 7) * 16;
  h_epilogue(d0, sc[0], sc[1], addr);
  h_epilogue(d1, sc[2], sc[3], addr + 1024);
  fence_async_smem();
  warp_arrive(bars + 8 * (B_HW + (N0 ? 1 : 0)));
  TR(N0 ? 21 : 19);
}

__global__ void __launch_bounds__(512, 1)
fused_kernel(const __grid_constant__ Maps maps, const char* __restrict__ x, const char* __restrict__ wqkv,
             const char* __restrict__ wo, const char* __restrict__ w1, const char* __restrict__ w2,
             const char* __restrict__ gate_w) {
  extern __shared__ __align__(1024) unsigned char smem[];
  const uint32_t sb = (uint32_t)__cvta_generic_to_shared(smem);
  const uint32_t bars = sb + SM_BAR;
  const int warp = __shfl_sync(0xffffffffu, threadIdx.x >> 5, 0);
  const int lane = threadIdx.x & 31;
  const int rb = blockIdx.x >> 3, r = blockIdx.x & 7;
  TR(warp == 0 ? 0 : 63);

  if (threadIdx.x < B_COUNT) {
    const int i = threadIdx.x;
    int cnt = 1;
    if (i < B_QFULL || (i >= B_W1FULL + 12 && i < B_HALO)) cnt = 2;
    else if ((i >= B_AKV && i < B_F1) || (i >= B_HEAD && i < B_HW)) cnt = 8;
    else if ((i >= B_F1 && i < B_HEAD) || (i >= B_HW && i < B_HFREE) || i == B_GRDY) cnt = 4;
    asm volatile("mbarrier.init.shared::cta.b64 [%0], %1;" ::"r"(bars + 8 * i), "r"(cnt) : "memory");
    fence_async_smem();
  } else if (warp == 15) {
    if (lane < 8) asm volatile("prefetch.tensormap [%0];" ::"l"((const char*)&maps + lane * 128) : "memory");
    if (lane == 8) l2_prefetch(x + blockIdx.x * 16384, 16384);
    if (lane == 9) l2_prefetch(wqkv + blockIdx.x * 12288, 12288);
  }
  __syncthreads();

  if (warp >= 12) {
    asm volatile("setmaxnreg.dec.sync.aligned.u32 32;");
    const unsigned epoch = g_epoch[blockIdx.x] + 1;
    if (warp == 12) {
      if (elect()) {
#pragma unroll 1
        for (int j = 0; j < 8; j++) {
          if (j >= 6) mbar_wait(bars + 8 * (B_AKV + j - 6));
          mbar_expect(bars + 8 * (B_KVFULL + j), 16384);
          tma3d(sb + SM_U + (j % 6) * 16384, &maps.wkv, 64 * r, 64 * j, 1, bars + 8 * (B_KVFULL + j));
        }
        const CUtensorMap* mb = ((r & 1) && r < 7) ? &maps.w1s : &maps.w1a;
        const int cb = r < 7 ? (768 + 80 * r) >> 5 : 41;
#pragma unroll 1
        for (int n = 0; n < 16; n++) {
          mbar_wait(bars + 8 * (n < 3 ? B_AKV + 2 + n : B_F1 + n - 3));
          mbar_expect(bars + 8 * (B_W1FULL + n), 12288);
          if (n < 8) tma3d(sb + SM_V + (n % 3) * 12288, &maps.w1a, 0, 64 * n, 3 * r, bars + 8 * (B_W1FULL + n));
          else tma3d(sb + SM_V + (n % 3) * 12288, mb, 0, 64 * ((n + 4) & 7), cb, bars + 8 * (B_W1FULL + n));
        }
#pragma unroll 1
        for (int s = 0; s < 30; s++) {
          const int i = s % 6;
          mbar_wait(bars + 8 * (s >= 6 ? B_F2 + s - 6 : s == 5 ? B_HFREE + 1 : B_F1 + 13 + ((s + 1) >> 1)));
          const uint32_t dst = sb + SM_V + (i == 5 ? 5 : (i + 2) % 5) * 8192;
          mbar_expect(bars + 8 * (B_G2FULL + s), 8192);
          if (s < 22) tma2d(dst, &maps.w2, 64 * r, 64 * s, bars + 8 * (B_G2FULL + s));
          else tma3d(dst, &maps.wo, 64 * r, 16 * ((s - 22) >> 1), 4 * (s & 1), bars + 8 * (B_G2FULL + s));
        }
      }
    } else if (warp == 13) {
      if (elect()) {
#pragma unroll 1
        for (int j = 0; j < 8; j++) {
          mbar_expect(bars + 8 * (B_KVFULL + j), 16384);
          tma2d(sb + SM_X + j * 16384, &maps.x, 64 * j, 128 * rb, bars + 8 * (B_KVFULL + j));
        }
#pragma unroll 1
        for (int j = 0; j < 8; j++) {
          mbar_wait(bars + 8 * (j >= 3 ? B_AQ + j - 3 : j == 0 ? B_AKV + 4 : B_AKV + 5));
          mbar_expect(bars + 8 * (B_QFULL + j), 8192);
          tma2d(sb + SM_T + (j % 3) * 8192, &maps.wq, 64 * r, 64 * j, bars + 8 * (B_QFULL + j));
        }
        mbar_wait(bars + 8 * (B_AQ + 7));
#pragma unroll 1
        for (int j = 0; j < 4; j++) {
          mbar_wait(bars + 8 * (B_F1 + 8 + j));
          mbar_expect(bars + 8 * (B_W1FULL + 12 + j), 16384);
          tma2d(sb + SM_X + (4 + j) * 16384, &maps.x, 64 * j, 128 * rb, bars + 8 * (B_W1FULL + 12 + j));
        }
        const char* a2 = (const char*)g_a2 + (size_t)rb * A2_BYTES;
        const unsigned* cnt = g_cnt + rb * 256;
#pragma unroll 1
        for (int s = 0; s < 30; s++) {
          const int i = s % 6;
          if (s == 0) { flag_wait(cnt, 8 * epoch); TR(40); }
          else if (s == 12) { flag_wait(cnt + 32, 8 * epoch); TR(41); }
          else if (s >= 22 && !(s & 1)) { flag_wait(cnt + 64 + 16 * (s - 22), 8 * epoch); TR(42 + (s - 22) / 2); }
          mbar_wait(bars + 8 * (s >= 6 ? B_F2 + s - 6 : s >= 4 ? B_HEAD + s - 4 : B_F1 + 12 + s));
          const uint32_t bytes = s == 21 ? 8192 : 16384;
          mbar_expect(bars + 8 * (B_G2FULL + s), bytes);
          bulk_load(sb + SM_X + ((i + 4) & 7) * 16384, a2 + s * 16384 - (s > 21 ? 8192 : 0), bytes, bars + 8 * (B_G2FULL + s));
        }
      }
    } else if (warp == 14) {
      if (elect()) {
        mbar_wait(bars + 8 * B_KVW);
        bulk_store((char*)g_kv + (size_t)blockIdx.x * 32768, sb + SM_L, 32768);
        bulk_commit_wait();
        flag_add(g_kvflag + blockIdx.x * 32);
        TR(48);
        const char* p1 = (const char*)g_zero;
        const char* p2 = (const char*)g_zero;
        int s1 = 0, s2 = 0;
        if (rb >= 1) { flag_wait(g_kvflag + (blockIdx.x - 8) * 32, epoch); p1 = (const char*)g_kv + (size_t)(blockIdx.x - 8) * 32768; s1 = 8192; }
        if (rb >= 2) { flag_wait(g_kvflag + (blockIdx.x - 16) * 32, epoch); p2 = (const char*)g_kv + (size_t)(blockIdx.x - 16) * 32768; s2 = 8192; }
        TR(49);
#pragma unroll 1
        for (int h = 0; h < 4; h++) {
          mbar_wait(bars + 8 * (B_AQ + h));
          mbar_wait(bars + 8 * (B_F1 + h));
          mbar_expect(bars + 8 * (B_HALO + h), 16384);
          bulk_load(sb + SM_X + h * 16384, p2 + h * s2, 8192, bars + 8 * (B_HALO + h));
          bulk_load(sb + SM_X + h * 16384 + 8192, p1 + h * s1, 8192, bars + 8 * (B_HALO + h));
        }
#pragma unroll 1
        for (int h = 0; h < 4; h++) {
          mbar_wait(bars + 8 * (B_HEAD + h));
          flag_add(g_cnt + rb * 256 + 64 + 32 * h);
        }
        TR(50);
      }
    } else {
      if (elect()) {
        mbar_expect(bars + 8 * B_GWFULL, 1024);
        bulk_load(sb + SM_GW, gate_w, 1024, bars + 8 * B_GWFULL);
        mbar_wait(bars + 8 * B_KVFULL);
        l2_prefetch(w1 + blockIdx.x * 11008, 11008);
        mbar_wait(bars + 8 * (B_AKV + 4));
        l2_prefetch(w2 + blockIdx.x * 11008, 11008);
        l2_prefetch(wo + blockIdx.x * 4096, 4096);
        char* a2 = (char*)g_a2 + (size_t)rb * A2_BYTES;
        mbar_wait(bars + 8 * B_HW);
        bulk_store(a2 + r * 12 * 2048, sb + SM_T, 12 * 2048);
        bulk_commit_wait();
        mbar_arrive(bars + 8 * B_HFREE);
        flag_add(g_cnt + rb * 256);
        TR(52);
        mbar_wait(bars + 8 * (B_HW + 1));
        if (r < 7) bulk_store(a2 + (96 + 10 * r) * 2048, sb + SM_T, 10 * 2048);
        else bulk_store(a2 + 166 * 2048, sb + SM_T + 2 * 2048, 6 * 2048);
        bulk_commit_wait();
        mbar_arrive(bars + 8 * (B_HFREE + 1));
        flag_add(g_cnt + rb * 256 + 32);
        TR(53);
        g_epoch[blockIdx.x] = epoch;
      }
    }
  } else if (warp >= 8) {
    const int wq = warp & 3, t = threadIdx.x & 127;
    {
      float z0 = 0.f, z1 = 0.f;
      mbar_wait(bars + 8 * B_GWFULL);
#pragma unroll 1
      for (int j = 0; j < 8; j++) {
        mbar_wait(bars + 8 * (B_KVFULL + j));
#pragma unroll
        for (int c = 0; c < 8; c++) {
          const uint4 xv = lds_v4(sb + SM_X + j * 16384 + t * 128 + ((c ^ (t & 7)) << 4));
          const uint4 wv = lds_v4(sb + SM_GW + (j * 8 + c) * 16);
          const uint32_t xa[4] = {xv.x, xv.y, xv.z, xv.w}, wa[4] = {wv.x, wv.y, wv.z, wv.w};
#pragma unroll
          for (int e = 0; e < 4; e++) {
            z0 = fmaf(__uint_as_float(xa[e] << 16), __uint_as_float(wa[e] << 16), z0);
            z1 = fmaf(__uint_as_float(xa[e] & 0xffff0000u), __uint_as_float(wa[e] & 0xffff0000u), z1);
          }
        }
      }
      const float g = 1.f / (1.f + __expf(-(z0 + z1)));
      asm volatile("st.shared.f32 [%0], %1;" ::"r"(sb + SM_G + t * 4), "f"(g) : "memory");
      warp_arrive(bars + 8 * B_GRDY);
    }
    TR(16);
    mbar_wait(bars + 8 * B_GRDY);
    float sc[4];
#pragma unroll
    for (int i = 0; i < 4; i++) sc[i] = 1.f - lds_f32(sb + SM_G + ((i >> 1) * 64 + 16 * wq + (lane >> 2) + (i & 1) * 8) * 4);
    mbar_wait(bars + 8 * (B_AKV + 6));
    TR(17);
    ffn1_half<48, 0>(sb, sc, lane, wq);
    ffn1_half<40, 8>(sb, sc, lane, wq);

    float d0[32], d1[32];
#pragma unroll
    for (int i = 0; i < 32; i++) { d0[i] = 0.f; d1[i] = 0.f; }
    int i6 = 0;
#pragma unroll 1
    for (int s = 0; s < 30; s++) {
      const uint32_t alo = ((sb + SM_X + ((i6 + 4) & 7) * 16384) >> 4) + LO_A2;
      const uint32_t blo = ((sb + SM_V + (i6 == 5 ? 5 : i6 >= 3 ? i6 - 3 : i6 + 2) * 8192) >> 4) + LO_W128;
      mbar_wait(bars + 8 * (B_G2FULL + s));
      const uint32_t prev = s > 0 ? bars + 8 * (B_F2 + s - 1) : 0;
      if (s == 21) f_kblock<32, 256, HI_A2, 64, 128, HI_SW128, 2>(d0, d1, alo, blo, 1, prev);
      else f_kblock<32, 256, HI_A2, 64, 128, HI_SW128, 4>(d0, d1, alo, blo, 1, prev);
      i6 = i6 == 5 ? 0 : i6 + 1;
    }
    WG_WAIT(0);
    pin(d0); pin(d1);
    TR(26);
    {
      const int row = 16 * wq + (lane & 15);
      const uint32_t base = sb + SM_X + 2 * 16384 + row * 128;
#pragma unroll
      for (int j = 0; j < 8; j += 2) {
        const uint32_t a = base + (((j + (lane >> 4)) ^ (row & 7)) << 4);
        stsm4(a, pack(d0[4 * j], d0[4 * j + 1]), pack(d0[4 * j + 2], d0[4 * j + 3]), pack(d0[4 * j + 4], d0[4 * j + 5]), pack(d0[4 * j + 6], d0[4 * j + 7]));
        stsm4(a + 8192, pack(d1[4 * j], d1[4 * j + 1]), pack(d1[4 * j + 2], d1[4 * j + 3]), pack(d1[4 * j + 4], d1[4 * j + 5]), pack(d1[4 * j + 6], d1[4 * j + 7]));
      }
      fence_async_smem();
      asm volatile("bar.sync 2, 128;" ::: "memory");
      if (wq == 0 && elect()) {
        asm volatile("cp.async.bulk.tensor.2d.global.shared::cta.bulk_group [%0, {%2, %3}], [%1];"
                     ::"l"(&maps.out), "r"(sb + SM_X + 2 * 16384), "r"(64 * r), "r"(128 * rb) : "memory");
        asm volatile("cp.async.bulk.commit_group;\n cp.async.bulk.wait_group.read 0;" ::: "memory");
      }
    }
    TR(27);
  } else {
    asm volatile("setmaxnreg.inc.sync.aligned.u32 176;");
    const int wg = warp >> 2, wq = warp & 3;
    uint32_t Q[4][4];
    {
      float d[64];
#pragma unroll
      for (int i = 0; i < 64; i++) d[i] = 0.f;
#pragma unroll 1
      for (int j = 0; j < 8; j++) {
        const uint32_t alo = ((sb + SM_X + j * 16384 + wg * 8192) >> 4) + LO_X;
        const uint32_t blo = ((sb + SM_U + (j >= 6 ? j - 6 : j) * 16384) >> 4) + LO_W128;
        mbar_wait(bars + 8 * (B_KVFULL + j));
        WG_FENCE();
        wgmma_ss<0, HI_SW128, 0, HI_SW128>(d, alo, blo, 1);
        wgmma_ss<2, HI_SW128, 128, HI_SW128>(d, alo, blo, 1);
        wgmma_ss<4, HI_SW128, 256, HI_SW128>(d, alo, blo, 1);
        wgmma_ss<6, HI_SW128, 384, HI_SW128>(d, alo, blo, 1);
        WG_COMMIT();
        WG_WAIT(1);
        if (j > 0) warp_arrive(bars + 8 * (B_AKV + j - 1));
      }
      WG_WAIT(0);
      pin(d);
      asm volatile("bar.sync 1, 256;" ::: "memory");
      TR(2 + 8 * wg);
      const uint32_t addr = sb + SM_L + (8 * wg + 2 * wq) * 512 + lane * 16;
#pragma unroll
      for (int h = 0; h < 4; h++)
#pragma unroll
        for (int rh = 0; rh < 2; rh++)
          stsm4(addr + h * 8192 + rh * 512,
                pack(d[8 * h + 2 * rh], d[8 * h + 2 * rh + 1]), pack(d[8 * h + 4 + 2 * rh], d[8 * h + 5 + 2 * rh]),
                pack(d[32 + 8 * h + 2 * rh], d[33 + 8 * h + 2 * rh]), pack(d[36 + 8 * h + 2 * rh], d[37 + 8 * h + 2 * rh]));
      fence_async_smem();
      warp_arrive(bars + 8 * B_KVW);
    }
    {
      float d[32];
#pragma unroll
      for (int i = 0; i < 32; i++) d[i] = 0.f;
#pragma unroll 1
      for (int j = 0; j < 8; j++) {
        const uint32_t alo = ((sb + SM_X + j * 16384 + wg * 8192) >> 4) + LO_X;
        const uint32_t blo = ((sb + SM_T + (j % 3) * 8192) >> 4) + LO_W128;
        mbar_wait(bars + 8 * (B_QFULL + j));
        WG_FENCE();
        wgmma_ss<0, HI_SW128, 0, HI_SW128>(d, alo, blo, 1);
        wgmma_ss<2, HI_SW128, 128, HI_SW128>(d, alo, blo, 1);
        wgmma_ss<4, HI_SW128, 256, HI_SW128>(d, alo, blo, 1);
        wgmma_ss<6, HI_SW128, 384, HI_SW128>(d, alo, blo, 1);
        WG_COMMIT();
        WG_WAIT(1);
        if (j > 0) warp_arrive(bars + 8 * (B_AQ + j - 1));
      }
      WG_WAIT(0);
      pin(d);
      warp_arrive(bars + 8 * (B_AQ + 7));
#pragma unroll
      for (int h = 0; h < 4; h++)
#pragma unroll
        for (int i = 0; i < 4; i++) Q[h][i] = pack(d[8 * h + 2 * i] * QSCALE, d[8 * h + 2 * i + 1] * QSCALE);
    }
    TR(3 + 8 * wg);
    const int T = 2 * rb + wg;
    const bool has_e = T >= 4;
    const float v1 = T >= 1 ? 1.f : 0.f, v2 = T >= 2 ? 1.f : 0.f, v3 = T >= 3 ? 1.f : 0.f;
    const int r0 = 16 * wq + (lane >> 2) - 2 * (lane & 3);
    uint32_t aH = (sb + SM_X + wg * 4096) >> 4;
    uint32_t aD = (sb + SM_L + wg * 4096) >> 4;
    uint32_t aF = (wg ? sb + SM_L : sb + SM_X + 12288) >> 4;
    const uint32_t sF = wg ? 512 : 1024;
    mbar_wait(bars + 8 * B_GRDY);
    const float g0 = lds_f32(sb + SM_G + (64 * wg + 16 * wq + (lane >> 2)) * 4);
    const float g1 = lds_f32(sb + SM_G + (64 * wg + 16 * wq + (lane >> 2) + 8) * 4);
    uint32_t* optr = (uint32_t*)((char*)g_a2 + (size_t)rb * A2_BYTES + (172 + 2 * r) * 2048 + (8 * wg + 2 * wq) * 128) + lane;
    uint32_t bad = 0;
    mbar_wait(bars + 8 * B_KVW);
    mbar_wait(bars + 8 * B_HALO);
    TR(4 + 8 * wg);
    {
      float SA[32], SB[32], SC[32], O[8], l0 = 0.f, l1 = 0.f;
      uint32_t P[16];
      WG_FENCE();
      wgmma_qk<0>(SA, Q[0], aD); wgmma_qk<0>(SC, Q[0], aH); wgmma_qk<0>(SB, Q[0], aF);
      WG_COMMIT(); WG_WAIT(0);
      pin(SA); pin(SB); pin(SC);
      merge(SA, SC, r0, has_e);
      fexp<0, 32>(SA, l0, l1);
#define PINL(a, b) asm volatile("" : "+f"(a), "+f"(b)::"memory")
#pragma unroll 1
      for (int h = 0; h < 4; h++) {
        float t0, t1;
        uint32_t PE[16];
        packp(P, SA);
#pragma unroll
        for (int j = 0; j < 8; j++) {
          const uint32_t k0 = pmask(8 * j, r0), k1 = pmask(8 * j, r0 + 8);
          PE[2 * j] = P[2 * j] & ~k0; P[2 * j] &= k0;
          PE[2 * j + 1] = P[2 * j + 1] & ~k1; P[2 * j + 1] &= k1;
        }
        pin(P); pin(PE);
        WG_FENCE();
        pv_tile<0, 0>(O, P, aD); pv_tile<0, 1>(O, PE, aH); wgmma_qk<512>(SA, Q[0], aH);
        WG_COMMIT(); SCHED_BAR();
        t0 = 0.f; t1 = 0.f;
        fexp<0, SPLIT>(SB, t0, t1); PINL(t0, t1); SCHED_BAR();
        WG_WAIT(0); pin(SA); pin(O); pin(P); pin(PE);
        fexp<SPLIT, 32>(SB, t0, t1); packp(P, SB); pin(P);
        l0 = fmaf(t0, v1, l0); l1 = fmaf(t1, v1, l1);
        WG_FENCE();
        pv_tile<0, 1>(O, P, aF); wgmma_qk<256>(SB, Q[0], aH);
        WG_COMMIT(); SCHED_BAR();
        t0 = 0.f; t1 = 0.f;
        fexp<0, SPLIT>(SA, t0, t1); PINL(t0, t1); SCHED_BAR();
        WG_WAIT(0); pin(SB); pin(O); pin(P);
        fexp<SPLIT, 32>(SA, t0, t1); packp(P, SA); pin(P);
        l0 = fmaf(t0, v2, l0); l1 = fmaf(t1, v2, l1);
        const int more = h < 3;
        const uint32_t nH = aH + (more ? 1024 : 0), nD = aD + (more ? 512 : 0), nF = aF + (more ? sF : 0);
        mbar_wait(bars + 8 * (B_HALO + h + more));
        WG_FENCE();
        pv_tile<512, 1>(O, P, aH); wgmma_qk<0>(SA, Q[1], nD); wgmma_qk<0>(SC, Q[1], nH);
        WG_COMMIT(); SCHED_BAR();
        t0 = 0.f; t1 = 0.f;
        fexp<0, SPLIT>(SB, t0, t1); PINL(t0, t1); SCHED_BAR();
        WG_WAIT(0); pin(SA); pin(SC); pin(O); pin(P);
        fexp<SPLIT, 32>(SB, t0, t1); packp(P, SB); pin(P);
        l0 = fmaf(t0, v3, l0); l1 = fmaf(t1, v3, l1);
        WG_FENCE();
        pv_tile<256, 1>(O, P, aH); wgmma_qk<0>(SB, Q[1], nF);
        WG_COMMIT(); SCHED_BAR();
        const float s0 = quad_sum(l0), s1 = quad_sum(l1);
        const float i0 = __fdividef(g0, s0), i1 = __fdividef(g1, s1);
        l0 = 0.f; l1 = 0.f;
        merge(SA, SC, r0, has_e);
        fexp<0, 32>(SA, l0, l1); PINL(l0, l1); SCHED_BAR();
        WG_WAIT(0); pin(SB); pin(O); pin(P);
        float am = fmaxf(fmaxf(fmaxf(fabsf(O[0]), fabsf(O[1])), fmaxf(fabsf(O[2]), fabsf(O[3]))),
                         fmaxf(fmaxf(fabsf(O[4]), fabsf(O[5])), fmaxf(fabsf(O[6]), fabsf(O[7]))));
        const bool ok = fminf(s0, s1) >= 0x1p-30f && s0 <= 0x1p60f && s1 <= 0x1p60f && am <= 0x1p120f;
        if (__all_sync(0xffffffffu, ok)) {
          optr[0] = pack(O[0] * i0, O[1] * i0); optr[32] = pack(O[2] * i1, O[3] * i1);
          optr[512] = pack(O[4] * i0, O[5] * i0); optr[544] = pack(O[6] * i1, O[7] * i1);
          warp_arrive(bars + 8 * (B_HEAD + h));
        } else {
          bad |= 1u << h;
        }
        optr += 16 * 512;
#pragma unroll
        for (int i = 0; i < 4; i++) { const uint32_t q = Q[0][i]; Q[0][i] = Q[1][i]; Q[1][i] = Q[2][i]; Q[2][i] = Q[3][i]; Q[3][i] = q; }
        aH = nH; aD = nD; aF = nF;
      }
    }
#pragma unroll 1
    for (int h = 0; h < 4; h++) {
      uint32_t any;
      asm volatile("{.reg .pred p, q; setp.ne.u32 p, %1, 0; barrier.red.or.pred.aligned q, %2, 128, p; selp.u32 %0, 1, 0, q;}"
                   : "=r"(any) : "r"(bad & (1u << h)), "r"(3 + wg) : "memory");
      if (any) {
        float S[32], O[8], m0 = -INFINITY, m1 = -INFINITY, l0 = 0.f, l1 = 0.f;
#pragma unroll
        for (int i = 0; i < 8; i++) O[i] = 0.f;
        const int nt = T >= 4 ? 5 : T + 1;
#pragma unroll 1
        for (int it = 0; it < 2 * nt; it++) {
          const int k = it >= nt ? it - nt : it;
          const int ti = wg + 4 - k;
          const uint32_t a = (ti >= 4 ? sb + SM_L + h * 8192 + (ti - 4) * 4096 : sb + SM_X + h * 16384 + ti * 4096) >> 4;
          const int hi = k == 0 ? r0 : 1000, lo = k == 4 ? r0 : -1000;
          WG_FENCE();
          wgmma_qk<0>(S, Q[0], a);
          WG_COMMIT(); WG_WAIT(0);
          pin(S);
          if (it == nt) { m0 = quad_max(m0); m1 = quad_max(m1); }
          uint32_t P[16];
#pragma unroll
          for (int i = 0; i < 32; i++) {
            const int c = 8 * (i >> 2) + (i & 1) - 4 * (i & 2);
            const float s = (c <= hi && c > lo) ? S[i] : -INFINITY;
            if (i & 2) { S[i] = ex2(s - m1); m1 = fmaxf(m1, s); } else { S[i] = ex2(s - m0); m0 = fmaxf(m0, s); }
          }
          if (it >= nt) {
#pragma unroll
            for (int i = 0; i < 32; i += 4) { l0 += S[i] + S[i + 1]; l1 += S[i + 2] + S[i + 3]; }
            packp(P, S);
            pin(P);
            WG_FENCE();
            pv_tile<0, 1>(O, P, a);
            WG_COMMIT(); WG_WAIT(0);
            pin(O); pin(P);
          }
        }
        const float i0 = g0 / quad_sum(l0), i1 = g1 / quad_sum(l1);
        if (bad & (1u << h)) {
          uint32_t* op = optr - (4 - h) * 16 * 512;
          op[0] = pack(O[0] * i0, O[1] * i0); op[32] = pack(O[2] * i1, O[3] * i1);
          op[512] = pack(O[4] * i0, O[5] * i0); op[544] = pack(O[6] * i1, O[7] * i1);
          warp_arrive(bars + 8 * (B_HEAD + h));
        }
      }
#pragma unroll
      for (int i = 0; i < 4; i++) { Q[0][i] = Q[1][i]; Q[1][i] = Q[2][i]; Q[2][i] = Q[3][i]; }
    }
  }
}

typedef CUresult (*EncodeFn)(CUtensorMap*, CUtensorMapDataType, cuuint32_t, void*, const cuuint64_t*, const cuuint64_t*,
                             const cuuint32_t*, const cuuint32_t*, CUtensorMapInterleave, CUtensorMapSwizzle,
                             CUtensorMapL2promotion, CUtensorMapFloatOOBfill);

void encode(EncodeFn fn, CUtensorMap* m, const void* p, int rank, cuuint64_t d0, cuuint64_t d1, cuuint64_t d2,
            cuuint64_t s1, cuuint64_t s2, cuuint32_t b0, cuuint32_t b1, cuuint32_t b2, CUtensorMapSwizzle sw) {
  const cuuint64_t gd[3] = {d0, d1, d2}, gs[2] = {s1, s2};
  const cuuint32_t bd[3] = {b0, b1, b2}, es[3] = {1, 1, 1};
  fn(m, CU_TENSOR_MAP_DATA_TYPE_BFLOAT16, rank, (void*)p, gd, gs, bd, es, CU_TENSOR_MAP_INTERLEAVE_NONE, sw,
     CU_TENSOR_MAP_L2_PROMOTION_L2_128B, CU_TENSOR_MAP_FLOAT_OOB_FILL_NONE);
}

}

extern "C" void kernel_launch(void* const* d_in, const int* in_sizes, int n_in, void* d_out, int out_size) {
  const char* x = (const char*)d_in[0];
  const char* wqkv = (const char*)d_in[1];
  const char* wo = (const char*)d_in[2];
  const char* w1 = (const char*)d_in[4];
  const char* w2 = (const char*)d_in[5];
  const char* gw = (const char*)d_in[6];
  void* fp = nullptr;
  cudaDriverEntryPointQueryResult q;
  cudaGetDriverEntryPoint("cuTensorMapEncodeTiled", &fp, cudaEnableDefault, &q);
  EncodeFn fn = (EncodeFn)fp;
  Maps m;
  const CUtensorMapSwizzle S128 = CU_TENSOR_MAP_SWIZZLE_128B, S64 = CU_TENSOR_MAP_SWIZZLE_64B;
  encode(fn, &m.x, x, 2, D_, S_, 1, D_ * 2, 0, 64, 128, 1, S128);
  encode(fn, &m.wkv, wqkv, 3, D_, D_, 3, 3 * D_ * 2, D_ * 2, 64, 64, 2, S128);
  encode(fn, &m.wq, wqkv, 2, D_, D_, 1, 3 * D_ * 2, 0, 64, 64, 1, S128);
  encode(fn, &m.w1a, w1, 3, 32, D_, 43, DFF * 2, 64, 32, 64, 3, S64);
  encode(fn, &m.w1s, w1 + 32, 3, 32, D_, 42, DFF * 2, 64, 32, 64, 3, S64);
  encode(fn, &m.w2, w2, 2, D_, DFF, 1, D_ * 2, 0, 64, 64, 1, S128);
  encode(fn, &m.wo, wo, 3, D_, 64, 8, D_ * 2, 64 * D_ * 2, 64, 16, 4, S128);
  encode(fn, &m.out, d_out, 2, D_, S_, 1, D_ * 2, 0, 64, 128, 1, S128);
  cudaFuncSetAttribute(fused_kernel, cudaFuncAttributeMaxDynamicSharedMemorySize, SM_TOTAL);
  fused_kernel<<<128, 512, SM_TOTAL>>>(m, x, wqkv, wo, w1, w2, gw);
}
```

```cpp
#include <cuda_runtime.h>
#include <cuda_bf16.h>
#include <cuda.h>
#include <stdint.h>

namespace {

constexpr int S_ = 2048, D_ = 512, DFF = 1376;
#define NA 80
constexpr int NB = 176 - NA, SA = NA / 8;
constexpr int A2_BYTES = 240 * 2048;
__host__ __device__ constexpr int kg_o(int h) { return h ? 176 + 16 * h : NA; }
constexpr float QSCALE = 0.25f * 1.4426950408889634f;

constexpr uint32_t SM_X = 0;
constexpr uint32_t SM_U = 131072;
constexpr uint32_t SM_W = SM_U;
constexpr uint32_t SM_L = SM_U + 49152;
constexpr uint32_t SM_H = SM_U + 81920;
__host__ __device__ constexpr uint32_t sm_halo(int h) { return (h & 1) ? SM_X + (h >> 1) * 16384 : SM_H; }
__host__ __device__ constexpr uint32_t sm_l(int h) { return SM_L + ((h + 2) & 3) * 8192; }
__host__ __device__ constexpr uint32_t sm_wo(int t) {
  return t < 2 ? sm_l(t) : t < 4 ? SM_X + (t - 2) * 8192 : t < 6 ? SM_H + (t - 4) * 8192 : sm_l(t - 4);
}
constexpr uint32_t SM_BAR = 229376;
constexpr uint32_t SM_G = SM_BAR + 1664;
constexpr uint32_t SM_TR = SM_G + 512;
constexpr uint32_t SM_TOTAL = SM_TR + 896;
static_assert(SM_TOTAL <= 232448, "smem");

enum : int {
  B_XFULL = 0, B_W2ND = 8,
  B_DUMMY = 16, B_ADUM = 17, B_INIT = 18, B_HALO = 28,
  B_W1FULL = 32,
  B_G2FULL = 48,
  B_AP = 80,
  B_KVG = 97, B_HEAD = 100, B_SLOT = 104, B_KVW = 105, B_HAF = 106,
  B_F1 = 112,
  B_F2 = 128, B_HW = 157, B_PRE = 159,
  B_GO = 170
};
#define BAR(i) (bars + 8 * (i))

struct Maps { CUtensorMap x, wqkv, w1a, w1s, w2, wo, out; };

struct Scratch {
  uint4 kv[128 * 2048];
  uint4 a2[16 * (A2_BYTES / 16)];
  uint4 zero[512];
  unsigned kvflag[128 * 32];
  unsigned rdy[16 * 64];
  uint2 gate[S_];
  unsigned epoch[128];
};
__device__ Scratch g_scratch;
#define TR(i)
#define TRD(i)

#define MERGE_EARLY 0
#define QPROM CU_TENSOR_MAP_L2_PROMOTION_L2_64B
#define H3AT 13
#define X0AT 10
#define WOAT 4
#define WOBT 9
#define NSA 12
#define NSB 8
#define POLLNS 0
#define TRB 5
#define MERGEF 1
#define CAP 0
#define ADAPT 0
#define PF2 1
#define PFLATE 0
#define MFMA 1
#define PFMA 1
#define OFFS 0
#define FAT 14
#define MERGE23 1
#define TRA 4
#define NSB2 8
#define KVWAT 3
#define KVT 2
#define OVL 1
#define EARLYREL 0
#define O0MODE 0
#define HELP1 1
#define O0AT 0
#define PAIRS 1
#define XSLOT 1
#define TAILN 1
#define PFOUT 0
#define KVPAUSE 9
#define PFAT 6
#define PF1AT 7
#define LAST4 0
#define EARLYS 2
#define HMUL 0
#define NEARLY 4
#define NMID 6
#define HALO1 0

__device__ __forceinline__ bool elect() {
  uint32_t p;
  asm volatile("{.reg .pred p; elect.sync _|p, 0xffffffff; selp.u32 %0, 1, 0, p;}" : "=r"(p));
  return p;
}
__device__ __forceinline__ void mbar_wait(uint32_t bar) {
  asm volatile("{.reg .pred p;\n LOOP_%=: mbarrier.try_wait.parity.shared::cta.b64 p, [%0], 0;\n @!p bra LOOP_%=;}" ::"r"(bar) : "memory");
}
__device__ __forceinline__ void mbar_wait_bounded(uint32_t bar) {
  asm volatile("{.reg .pred p; .reg .b32 c; .reg .b64 z; mov.b32 c, 0;\n"
               "LOOP_%=: add.u32 c, c, 1; setp.gt.u32 p, c, 2000000; mov.b64 z, 0; @p st.global.u32 [z], c;\n"
               "mbarrier.try_wait.parity.shared::cta.b64 p, [%0], 0;\n @!p bra LOOP_%=;}" ::"r"(bar) : "memory");
}
__device__ __forceinline__ uint32_t mbar_probe(uint32_t bar) {
  uint32_t ok;
  asm volatile("{.reg .pred p; mbarrier.test_wait.parity.shared::cta.b64 p, [%1], 0; selp.u32 %0, 1, 0, p;}" : "=r"(ok) : "r"(bar) : "memory");
  return ok;
}
__device__ __forceinline__ void mbar_finish(uint32_t bar, uint32_t ok) {
  asm volatile("{.reg .pred p; setp.ne.u32 p, %1, 0;\n @p bra.uni DONE_%=;\n"
               "LOOP_%=: mbarrier.try_wait.parity.shared::cta.b64 p, [%0], 0;\n @!p bra LOOP_%=;\n DONE_%=: }" ::"r"(bar), "r"(ok) : "memory");
}
__device__ __forceinline__ void mbar_arrive(uint32_t bar) {
  asm volatile("mbarrier.arrive.shared::cta.b64 _, [%0];" ::"r"(bar) : "memory");
}
__device__ __forceinline__ void warp_arrive(uint32_t bar) {
  asm volatile("{.reg .pred p; elect.sync _|p, 0xffffffff; @p mbarrier.arrive.shared::cta.b64 _, [%0];}" ::"r"(bar) : "memory");
}
__device__ __forceinline__ void pair_arrive(uint32_t bar, uint32_t peer) {
  asm volatile("{.reg .pred p; .reg .b32 a; setp.ne.u32 p, %1, 0xffffffff; add.u32 a, %0, %1;\n"
               "@p mbarrier.arrive.shared::cluster.b64 _, [a];}" ::"r"(bar), "r"(peer) : "memory");
}
__device__ __forceinline__ void cluster_sync() {
  asm volatile("barrier.cluster.arrive.relaxed.aligned;\n barrier.cluster.wait.aligned;" ::: "memory");
}
__device__ __forceinline__ uint32_t dsc(uint32_t addr) { return (addr & 0x3FFFF) >> 4; }
__device__ __forceinline__ void warp_publish(uint32_t bar) { __syncwarp(); warp_arrive(bar); }
__device__ __forceinline__ void warp_publish2(uint32_t bar) {
  __syncwarp();
  asm volatile("{.reg .pred p; elect.sync _|p, 0xffffffff; @p mbarrier.arrive.shared::cta.b64 _, [%0], 2;}" ::"r"(bar) : "memory");
}
__device__ __forceinline__ void mbar_init(uint32_t bar, uint32_t cnt) {
  asm volatile("mbarrier.init.shared::cta.b64 [%0], %1;" ::"r"(bar), "r"(cnt) : "memory");
}
__device__ __forceinline__ void mbar_expect(uint32_t bar, uint32_t bytes) {
  asm volatile("mbarrier.arrive.expect_tx.shared::cta.b64 _, [%0], %1;" ::"r"(bar), "r"(bytes) : "memory");
}
__device__ __forceinline__ void tma2d(uint32_t dst, const CUtensorMap* m, int c0, int c1, uint32_t bar) {
  asm volatile("cp.async.bulk.tensor.2d.shared::cluster.global.mbarrier::complete_tx::bytes [%0], [%1, {%3, %4}], [%2];"
               ::"r"(dst), "l"(m), "r"(bar), "r"(c0), "r"(c1) : "memory");
}
__device__ __forceinline__ void tma3d(uint32_t dst, const CUtensorMap* m, int c0, int c1, int c2, uint32_t bar) {
  asm volatile("cp.async.bulk.tensor.3d.shared::cluster.global.mbarrier::complete_tx::bytes [%0], [%1, {%3, %4, %5}], [%2];"
               ::"r"(dst), "l"(m), "r"(bar), "r"(c0), "r"(c1), "r"(c2) : "memory");
}
__device__ __forceinline__ void tma2d_mc(uint32_t dst, const CUtensorMap* m, int c0, int c1, uint32_t bar) {
  asm volatile("cp.async.bulk.tensor.2d.shared::cluster.global.mbarrier::complete_tx::bytes.multicast::cluster [%0], [%1, {%3, %4}], [%2], %5;"
               ::"r"(dst), "l"(m), "r"(bar), "r"(c0), "r"(c1), "h"((uint16_t)3) : "memory");
}
__device__ __forceinline__ void tma3d_mc(uint32_t dst, const CUtensorMap* m, int c0, int c1, int c2, uint32_t bar) {
  asm volatile("cp.async.bulk.tensor.3d.shared::cluster.global.mbarrier::complete_tx::bytes.multicast::cluster [%0], [%1, {%3, %4, %5}], [%2], %6;"
               ::"r"(dst), "l"(m), "r"(bar), "r"(c0), "r"(c1), "r"(c2), "h"((uint16_t)3) : "memory");
}
__device__ __forceinline__ void bulk_load(uint32_t dst, const void* src, uint32_t bytes, uint32_t bar) {
  asm volatile("cp.async.bulk.shared::cluster.global.mbarrier::complete_tx::bytes [%0], [%1], %2, [%3];"
               ::"r"(dst), "l"(src), "r"(bytes), "r"(bar) : "memory");
}
__device__ __forceinline__ void l2_prefetch(const void* p, uint32_t bytes) {
  asm volatile("cp.async.bulk.prefetch.L2.global [%0], %1;" ::"l"(p), "r"(bytes) : "memory");
}
__device__ __forceinline__ void fence_async_smem() { asm volatile("fence.proxy.async.shared::cta;" ::: "memory"); }
__device__ __forceinline__ void fence_async_all() { asm volatile("fence.proxy.async;" ::: "memory"); }
__device__ __forceinline__ void spin_guard(unsigned& it) {
  if (++it > (1u << 22)) asm volatile("st.global.u32 [%0], %1;" ::"l"(0ull), "r"(it) : "memory");
}
__device__ __forceinline__ unsigned ld_flag(const unsigned* f) {
  unsigned v; asm volatile("ld.relaxed.gpu.global.u32 %0, [%1];" : "=r"(v) : "l"(f) : "memory"); return v;
}
__device__ __forceinline__ void fence_async_global() { asm volatile("fence.proxy.async.global;" ::: "memory"); }
__device__ __forceinline__ void flag_wait2(const unsigned* f0, const unsigned* f1, unsigned target) {
  unsigned a, b, it = 0;
  do { a = ld_flag(f0); b = ld_flag(f1); spin_guard(it); } while ((int)(a - target) < 0 || (int)(b - target) < 0);
  fence_async_global();
}
__device__ __forceinline__ void flag_add(unsigned* f) {
  fence_async_all();
  asm volatile("red.relaxed.gpu.global.add.u32 [%0], 1;" ::"l"(f) : "memory");
}
__device__ __forceinline__ void flag_set(unsigned* f, unsigned v) {
  fence_async_all();
  asm volatile("st.relaxed.gpu.global.u32 [%0], %1;" ::"l"(f), "r"(v) : "memory");
}
__device__ __forceinline__ unsigned load_epoch(const Scratch* sc_) {
  unsigned v;
  asm volatile("ld.relaxed.gpu.global.u32 %0, [%1];" : "=r"(v) : "l"(sc_->epoch + blockIdx.x) : "memory");
  return v;
}
__device__ __forceinline__ float gate_of(const uint2* p, unsigned epoch) {
  float g; unsigned e, it = 0;
  do {
    asm volatile("ld.relaxed.gpu.global.v2.b32 {%0, %1}, [%2];" : "=f"(g), "=r"(e) : "l"(p) : "memory");
    spin_guard(it);
  } while (!__all_sync(0xffffffffu, e == epoch + 1));
  return g;
}
__device__ __forceinline__ void stsm4(uint32_t addr, uint32_t a, uint32_t b, uint32_t c, uint32_t d) {
  asm volatile("stmatrix.sync.aligned.m8n8.x4.shared.b16 [%0], {%1, %2, %3, %4};" ::"r"(addr), "r"(a), "r"(b), "r"(c), "r"(d) : "memory");
}
__device__ __forceinline__ uint32_t pack(float lo, float hi) {
  uint32_t r; asm("cvt.rn.bf16x2.f32 %0, %1, %2;" : "=r"(r) : "f"(hi), "f"(lo)); return r;
}
__device__ __forceinline__ uint32_t pack_relu(float lo, float hi) {
  uint32_t r; asm("cvt.rn.relu.bf16x2.f32 %0, %1, %2;" : "=r"(r) : "f"(hi), "f"(lo)); return r;
}
__device__ __forceinline__ float ex2(float x) { float y; asm("ex2.approx.ftz.f32 %0, %1;" : "=f"(y) : "f"(x)); return y; }
__device__ __forceinline__ float lds_f32(uint32_t a) { float v; asm volatile("ld.shared.f32 %0, [%1];" : "=f"(v) : "r"(a) : "memory"); return v; }
__device__ __forceinline__ uint4 lds_v4(uint32_t a) {
  uint4 v; asm volatile("ld.shared.v4.u32 {%0,%1,%2,%3}, [%4];" : "=r"(v.x), "=r"(v.y), "=r"(v.z), "=r"(v.w) : "r"(a) : "memory"); return v;
}
#define WG_FENCE() asm volatile("wgmma.fence.sync.aligned;" ::: "memory")
#define WG_COMMIT() asm volatile("wgmma.commit_group.sync.aligned;" ::: "memory")
#define WG_WAIT(n) asm volatile("wgmma.wait_group.sync.aligned " #n ";" ::: "memory")
#define SCHED_BAR() asm volatile("pmevent 1;" ::: "memory")
template <int N> __device__ __forceinline__ void pin(float (&d)[N]) {
#pragma unroll
  for (int i = 0; i < N; i++) asm volatile("" : "+f"(d[i])::"memory");
}
template <int N> __device__ __forceinline__ void pin(uint32_t (&d)[N]) {
#pragma unroll
  for (int i = 0; i < N; i++) asm volatile("" : "+r"(d[i])::"memory");
}

template <int LO, int HI, int N> __device__ __forceinline__ void pinr(float (&d)[N]) {
#pragma unroll
  for (int i = LO; i < HI; i++) asm volatile("" : "+f"(d[i])::"memory");
}
template <int LO, int HI, int N> __device__ __forceinline__ void pinr(uint32_t (&d)[N]) {
#pragma unroll
  for (int i = LO; i < HI; i++) asm volatile("" : "+r"(d[i])::"memory");
}

constexpr uint32_t HI_SW128 = (1024 >> 4) | (1u << 30);
constexpr uint32_t HI_SW64 = (512 >> 4) | (2u << 30);
constexpr uint32_t HI_A2 = (128 >> 4);
constexpr int LO_X = 1 << 16, LO_W128 = (8192 >> 4) << 16, LO_W64 = (4096 >> 4) << 16, LO_A2 = (2048 >> 4) << 16;

template <int AOFF, uint32_t AHI, int BOFF, uint32_t BHI, int TA = 0, int TB = 1>
__device__ __forceinline__ void wgmma_ss(float (&d)[40], uint32_t alo, uint32_t blo, int acc) {
  asm volatile("{.reg .pred p; .reg .b32 ta, tb; .reg .b64 da, db; setp.ne.b32 p, %42, 0;\n"
    "add.u32 ta, %40, %43; mov.b64 da, {ta, %44}; add.u32 tb, %41, %45; mov.b64 db, {tb, %46};\n"
    "wgmma.mma_async.sync.aligned.m64n80k16.f32.bf16.bf16 {%0,%1,%2,%3,%4,%5,%6,%7,%8,%9,%10,%11,%12,%13,%14,%15,%16,%17,%18,%19,%20,%21,%22,%23,%24,%25,%26,%27,%28,%29,%30,%31,%32,%33,%34,%35,%36,%37,%38,%39}, da, db, p, 1, 1, %47, %48;}"
    : "+f"(d[0]),"+f"(d[1]),"+f"(d[2]),"+f"(d[3]),"+f"(d[4]),"+f"(d[5]),"+f"(d[6]),"+f"(d[7]),"+f"(d[8]),"+f"(d[9]),"+f"(d[10]),"+f"(d[11]),"+f"(d[12]),"+f"(d[13]),"+f"(d[14]),"+f"(d[15]),"+f"(d[16]),"+f"(d[17]),"+f"(d[18]),"+f"(d[19]),"+f"(d[20]),"+f"(d[21]),"+f"(d[22]),"+f"(d[23]),"+f"(d[24]),"+f"(d[25]),"+f"(d[26]),"+f"(d[27]),"+f"(d[28]),"+f"(d[29]),"+f"(d[30]),"+f"(d[31]),"+f"(d[32]),"+f"(d[33]),"+f"(d[34]),"+f"(d[35]),"+f"(d[36]),"+f"(d[37]),"+f"(d[38]),"+f"(d[39])
    : "r"(alo), "r"(blo), "r"(acc), "n"(AOFF), "n"(AHI), "n"(BOFF), "n"(BHI), "n"(TA), "n"(TB));
}
template <int AOFF, uint32_t AHI, int BOFF, uint32_t BHI, int TA = 0, int TB = 1>
__device__ __forceinline__ void wgmma_ss(float (&d)[44], uint32_t alo, uint32_t blo, int acc) {
  asm volatile("{.reg .pred p; .reg .b32 ta, tb; .reg .b64 da, db; setp.ne.b32 p, %46, 0;\n"
    "add.u32 ta, %44, %47; mov.b64 da, {ta, %48}; add.u32 tb, %45, %49; mov.b64 db, {tb, %50};\n"
    "wgmma.mma_async.sync.aligned.m64n88k16.f32.bf16.bf16 {%0,%1,%2,%3,%4,%5,%6,%7,%8,%9,%10,%11,%12,%13,%14,%15,%16,%17,%18,%19,%20,%21,%22,%23,%24,%25,%26,%27,%28,%29,%30,%31,%32,%33,%34,%35,%36,%37,%38,%39,%40,%41,%42,%43}, da, db, p, 1, 1, %51, %52;}"
    : "+f"(d[0]),"+f"(d[1]),"+f"(d[2]),"+f"(d[3]),"+f"(d[4]),"+f"(d[5]),"+f"(d[6]),"+f"(d[7]),"+f"(d[8]),"+f"(d[9]),"+f"(d[10]),"+f"(d[11]),"+f"(d[12]),"+f"(d[13]),"+f"(d[14]),"+f"(d[15]),"+f"(d[16]),"+f"(d[17]),"+f"(d[18]),"+f"(d[19]),"+f"(d[20]),"+f"(d[21]),"+f"(d[22]),"+f"(d[23]),"+f"(d[24]),"+f"(d[25]),"+f"(d[26]),"+f"(d[27]),"+f"(d[28]),"+f"(d[29]),"+f"(d[30]),"+f"(d[31]),"+f"(d[32]),"+f"(d[33]),"+f"(d[34]),"+f"(d[35]),"+f"(d[36]),"+f"(d[37]),"+f"(d[38]),"+f"(d[39]),"+f"(d[40]),"+f"(d[41]),"+f"(d[42]),"+f"(d[43])
    : "r"(alo), "r"(blo), "r"(acc), "n"(AOFF), "n"(AHI), "n"(BOFF), "n"(BHI), "n"(TA), "n"(TB));
}
template <int AOFF, uint32_t AHI, int BOFF, uint32_t BHI, int TA = 0, int TB = 1>
__device__ __forceinline__ void wgmma_ss(float (&d)[48], uint32_t alo, uint32_t blo, int acc) {
  asm volatile("{.reg .pred p; .reg .b32 ta, tb; .reg .b64 da, db; setp.ne.b32 p, %50, 0;\n"
    "add.u32 ta, %48, %51; mov.b64 da, {ta, %52}; add.u32 tb, %49, %53; mov.b64 db, {tb, %54};\n"
    "wgmma.mma_async.sync.aligned.m64n96k16.f32.bf16.bf16 {%0,%1,%2,%3,%4,%5,%6,%7,%8,%9,%10,%11,%12,%13,%14,%15,%16,%17,%18,%19,%20,%21,%22,%23,%24,%25,%26,%27,%28,%29,%30,%31,%32,%33,%34,%35,%36,%37,%38,%39,%40,%41,%42,%43,%44,%45,%46,%47}, da, db, p, 1, 1, %55, %56;}"
    : "+f"(d[0]),"+f"(d[1]),"+f"(d[2]),"+f"(d[3]),"+f"(d[4]),"+f"(d[5]),"+f"(d[6]),"+f"(d[7]),"+f"(d[8]),"+f"(d[9]),"+f"(d[10]),"+f"(d[11]),"+f"(d[12]),"+f"(d[13]),"+f"(d[14]),"+f"(d[15]),"+f"(d[16]),"+f"(d[17]),"+f"(d[18]),"+f"(d[19]),"+f"(d[20]),"+f"(d[21]),"+f"(d[22]),"+f"(d[23]),"+f"(d[24]),"+f"(d[25]),"+f"(d[26]),"+f"(d[27]),"+f"(d[28]),"+f"(d[29]),"+f"(d[30]),"+f"(d[31]),"+f"(d[32]),"+f"(d[33]),"+f"(d[34]),"+f"(d[35]),"+f"(d[36]),"+f"(d[37]),"+f"(d[38]),"+f"(d[39]),"+f"(d[40]),"+f"(d[41]),"+f"(d[42]),"+f"(d[43]),"+f"(d[44]),"+f"(d[45]),"+f"(d[46]),"+f"(d[47])
    : "r"(alo), "r"(blo), "r"(acc), "n"(AOFF), "n"(AHI), "n"(BOFF), "n"(BHI), "n"(TA), "n"(TB));
}
template <int AOFF, uint32_t AHI, int BOFF, uint32_t BHI, int TA = 0, int TB = 1>
__device__ __forceinline__ void wgmma_ss(float (&d)[64], uint32_t alo, uint32_t blo, int acc) {
  asm volatile("{.reg .pred p; .reg .b32 ta, tb; .reg .b64 da, db; setp.ne.b32 p, %66, 0;\n"
    "add.u32 ta, %64, %67; mov.b64 da, {ta, %68}; add.u32 tb, %65, %69; mov.b64 db, {tb, %70};\n"
    "wgmma.mma_async.sync.aligned.m64n128k16.f32.bf16.bf16 {%0,%1,%2,%3,%4,%5,%6,%7,%8,%9,%10,%11,%12,%13,%14,%15,%16,%17,%18,%19,%20,%21,%22,%23,%24,%25,%26,%27,%28,%29,%30,%31,%32,%33,%34,%35,%36,%37,%38,%39,%40,%41,%42,%43,%44,%45,%46,%47,%48,%49,%50,%51,%52,%53,%54,%55,%56,%57,%58,%59,%60,%61,%62,%63}, da, db, p, 1, 1, %71, %72;}"
    : "+f"(d[0]),"+f"(d[1]),"+f"(d[2]),"+f"(d[3]),"+f"(d[4]),"+f"(d[5]),"+f"(d[6]),"+f"(d[7]),"+f"(d[8]),"+f"(d[9]),"+f"(d[10]),"+f"(d[11]),"+f"(d[12]),"+f"(d[13]),"+f"(d[14]),"+f"(d[15]),"+f"(d[16]),"+f"(d[17]),"+f"(d[18]),"+f"(d[19]),"+f"(d[20]),"+f"(d[21]),"+f"(d[22]),"+f"(d[23]),"+f"(d[24]),"+f"(d[25]),"+f"(d[26]),"+f"(d[27]),"+f"(d[28]),"+f"(d[29]),"+f"(d[30]),"+f"(d[31]),"+f"(d[32]),"+f"(d[33]),"+f"(d[34]),"+f"(d[35]),"+f"(d[36]),"+f"(d[37]),"+f"(d[38]),"+f"(d[39]),"+f"(d[40]),"+f"(d[41]),"+f"(d[42]),"+f"(d[43]),"+f"(d[44]),"+f"(d[45]),"+f"(d[46]),"+f"(d[47]),"+f"(d[48]),"+f"(d[49]),"+f"(d[50]),"+f"(d[51]),"+f"(d[52]),"+f"(d[53]),"+f"(d[54]),"+f"(d[55]),"+f"(d[56]),"+f"(d[57]),"+f"(d[58]),"+f"(d[59]),"+f"(d[60]),"+f"(d[61]),"+f"(d[62]),"+f"(d[63])
    : "r"(alo), "r"(blo), "r"(acc), "n"(AOFF), "n"(AHI), "n"(BOFF), "n"(BHI), "n"(TA), "n"(TB));
}
template <int OFF>
__device__ __forceinline__ void wgmma_qk(float (&d)[32], const uint32_t (&a)[4], uint32_t lo) {
  asm volatile("{.reg .b32 t; .reg .b64 db; add.u32 t, %36, %37; mov.b64 db, {t, 32};\n"
    "wgmma.mma_async.sync.aligned.m64n64k16.f32.bf16.bf16 {%0,%1,%2,%3,%4,%5,%6,%7,%8,%9,%10,%11,%12,%13,%14,%15,%16,%17,%18,%19,%20,%21,%22,%23,%24,%25,%26,%27,%28,%29,%30,%31}, {%32,%33,%34,%35}, db, 0, 1, 1, 0;}"
    : "=f"(d[0]),"=f"(d[1]),"=f"(d[2]),"=f"(d[3]),"=f"(d[4]),"=f"(d[5]),"=f"(d[6]),"=f"(d[7]),"=f"(d[8]),"=f"(d[9]),"=f"(d[10]),"=f"(d[11]),"=f"(d[12]),"=f"(d[13]),"=f"(d[14]),"=f"(d[15]),"=f"(d[16]),"=f"(d[17]),"=f"(d[18]),"=f"(d[19]),"=f"(d[20]),"=f"(d[21]),"=f"(d[22]),"=f"(d[23]),"=f"(d[24]),"=f"(d[25]),"=f"(d[26]),"=f"(d[27]),"=f"(d[28]),"=f"(d[29]),"=f"(d[30]),"=f"(d[31])
    : "r"(a[0]), "r"(a[1]), "r"(a[2]), "r"(a[3]), "r"(lo), "n"(OFF + (8 << 16)));
}
template <int OFF>
__device__ __forceinline__ void wgmma_qk_tied(float (&d)[32], const uint32_t (&a)[4], uint32_t lo) {
  asm volatile("{.reg .b32 t; .reg .b64 db; add.u32 t, %36, %37; mov.b64 db, {t, 32};\n"
    "wgmma.mma_async.sync.aligned.m64n64k16.f32.bf16.bf16 {%0,%1,%2,%3,%4,%5,%6,%7,%8,%9,%10,%11,%12,%13,%14,%15,%16,%17,%18,%19,%20,%21,%22,%23,%24,%25,%26,%27,%28,%29,%30,%31}, {%32,%33,%34,%35}, db, 0, 1, 1, 0;}"
    : "+f"(d[0]),"+f"(d[1]),"+f"(d[2]),"+f"(d[3]),"+f"(d[4]),"+f"(d[5]),"+f"(d[6]),"+f"(d[7]),"+f"(d[8]),"+f"(d[9]),"+f"(d[10]),"+f"(d[11]),"+f"(d[12]),"+f"(d[13]),"+f"(d[14]),"+f"(d[15]),"+f"(d[16]),"+f"(d[17]),"+f"(d[18]),"+f"(d[19]),"+f"(d[20]),"+f"(d[21]),"+f"(d[22]),"+f"(d[23]),"+f"(d[24]),"+f"(d[25]),"+f"(d[26]),"+f"(d[27]),"+f"(d[28]),"+f"(d[29]),"+f"(d[30]),"+f"(d[31])
    : "r"(a[0]), "r"(a[1]), "r"(a[2]), "r"(a[3]), "r"(lo), "n"(OFF + (8 << 16)));
}
template <int OFF, int ACC>
__device__ __forceinline__ void wgmma_pv(float (&d)[8], uint32_t a0, uint32_t a1, uint32_t a2, uint32_t a3, uint32_t lo) {
  if (ACC)
    asm volatile("{.reg .b32 t; .reg .b64 db; add.u32 t, %12, %13; mov.b64 db, {t, 8};\n"
      "wgmma.mma_async.sync.aligned.m64n16k16.f32.bf16.bf16 {%0,%1,%2,%3,%4,%5,%6,%7}, {%8,%9,%10,%11}, db, 1, 1, 1, 1;}"
      : "+f"(d[0]), "+f"(d[1]), "+f"(d[2]), "+f"(d[3]), "+f"(d[4]), "+f"(d[5]), "+f"(d[6]), "+f"(d[7])
      : "r"(a0), "r"(a1), "r"(a2), "r"(a3), "r"(lo), "n"(OFF + 16 + (32 << 16)));
  else
    asm volatile("{.reg .b32 t; .reg .b64 db; add.u32 t, %12, %13; mov.b64 db, {t, 8};\n"
      "wgmma.mma_async.sync.aligned.m64n16k16.f32.bf16.bf16 {%0,%1,%2,%3,%4,%5,%6,%7}, {%8,%9,%10,%11}, db, 0, 1, 1, 1;}"
      : "=f"(d[0]), "=f"(d[1]), "=f"(d[2]), "=f"(d[3]), "=f"(d[4]), "=f"(d[5]), "=f"(d[6]), "=f"(d[7])
      : "r"(a0), "r"(a1), "r"(a2), "r"(a3), "r"(lo), "n"(OFF + 16 + (32 << 16)));
}
template <int C> __device__ __forceinline__ uint32_t pmask(int r16) {
  uint32_t m;
  asm("shf.l.clamp.b32 %0, 0xffffffff, 0, %1;" : "=r"(m) : "r"(__viaddmax_s32(r16, -16 * C, 0)));
  return m;
}
__device__ __forceinline__ float quad_sum(float v) {
  v += __shfl_xor_sync(0xffffffffu, v, 1); v += __shfl_xor_sync(0xffffffffu, v, 2); return v;
}
__device__ __forceinline__ float quad_max(float v) {
  v = fmaxf(v, __shfl_xor_sync(0xffffffffu, v, 1)); v = fmaxf(v, __shfl_xor_sync(0xffffffffu, v, 2)); return v;
}

template <int O, int NREG, int NP>
__device__ __forceinline__ void h_pack(uint32_t (&p)[NP], const float (&d)[NREG], float sa, float sb) {
#pragma unroll
  for (int i = 0; i < NREG / 2; i++) {
    const float c = (i & 1) ? sb : sa;
    p[O + i] = pack_relu(d[2 * i] * c, d[2 * i + 1] * c);
  }
}
template <int LO, int HI, int NP>
__device__ __forceinline__ void h_store(const uint32_t (&p)[NP], uint32_t* hp, bool on = true) {
#pragma unroll
  for (int i = LO; i < HI && i < NP; i++) {
    const int m = i >= NP / 2, k = i - m * (NP / 2);
    if (on) hp[(k >> 1) * 512 + (k & 1) * 32 + m * 256] = p[i];
  }
}

struct F1 { uint32_t alo, blo, done, next; };
template <int LO, int STEP, int NREG, int NP>
__device__ __forceinline__ void f1_block(float (&d0)[NREG], float (&d1)[NREG], F1& f, uint32_t peer, int acc, int da, int db,
                                         const uint32_t (&p)[NP], uint32_t* hp) {
  WG_FENCE();
  wgmma_ss<0, HI_SW128, 0, HI_SW64>(d0, f.alo, f.blo, acc);
  wgmma_ss<512, HI_SW128, 0, HI_SW64>(d1, f.alo, f.blo, acc);
  WG_COMMIT();
  h_store<LO, LO + STEP>(p, hp);
  WG_WAIT(1);
  if (EARLYREL) pair_arrive(f.done, peer);
  wgmma_ss<2, HI_SW128, 64, HI_SW64>(d0, f.alo, f.blo, 1);
  wgmma_ss<514, HI_SW128, 64, HI_SW64>(d1, f.alo, f.blo, 1);
  WG_COMMIT();
  if (!EARLYREL) pair_arrive(f.done, peer);
  h_store<LO + STEP, LO + 2 * STEP>(p, hp);
  WG_WAIT(1);
  wgmma_ss<4, HI_SW128, 128, HI_SW64>(d0, f.alo, f.blo, 1);
  wgmma_ss<516, HI_SW128, 128, HI_SW64>(d1, f.alo, f.blo, 1);
  WG_COMMIT();
  const uint32_t ok = mbar_probe(f.next);
  h_store<LO + 2 * STEP, LO + 3 * STEP>(p, hp);
  WG_WAIT(1);
  wgmma_ss<6, HI_SW128, 192, HI_SW64>(d0, f.alo, f.blo, 1);
  wgmma_ss<518, HI_SW128, 192, HI_SW64>(d1, f.alo, f.blo, 1);
  WG_COMMIT();
  h_store<LO + 3 * STEP, LO + 4 * STEP>(p, hp);
  f.done = f.next + 8 * (B_F1 - B_W1FULL - 1);
  f.alo += da; f.blo += db;
  mbar_finish(f.next, ok);
  f.next += 8;
  WG_WAIT(1);
}
template <int NS, int NS2, bool HEADONLY = false, int NREG>
__device__ __forceinline__ void f1_last(float (&d0)[NREG], float (&d1)[NREG], F1& f, uint32_t peer, const float (&sc)[4],
                                        uint32_t (&p)[NREG], uint32_t* hp) {
  WG_FENCE();
  wgmma_ss<0, HI_SW128, 0, HI_SW64>(d0, f.alo, f.blo, 1);
  wgmma_ss<2, HI_SW128, 64, HI_SW64>(d0, f.alo, f.blo, 1);
  WG_COMMIT(); WG_WAIT(1);
  wgmma_ss<4, HI_SW128, 128, HI_SW64>(d0, f.alo, f.blo, 1);
  wgmma_ss<6, HI_SW128, 192, HI_SW64>(d0, f.alo, f.blo, 1);
  WG_COMMIT();
  pair_arrive(f.done, peer);
  WG_WAIT(1);
  wgmma_ss<512, HI_SW128, 0, HI_SW64>(d1, f.alo, f.blo, 1);
  wgmma_ss<514, HI_SW128, 64, HI_SW64>(d1, f.alo, f.blo, 1);
  wgmma_ss<516, HI_SW128, 128, HI_SW64>(d1, f.alo, f.blo, 1);
  wgmma_ss<518, HI_SW128, 192, HI_SW64>(d1, f.alo, f.blo, 1);
  WG_COMMIT();
  const uint32_t ok = mbar_probe(f.next);
  WG_WAIT(1);
  pin(d0);
  h_pack<0>(p, d0, sc[0], sc[1]);
  h_store<0, NS>(p, hp);
  pinr<NS, NREG / 2>(p);
  if (HEADONLY) { mbar_finish(f.next, ok); return; }
  SCHED_BAR();
  WG_WAIT(0);
  pin(d1);
  pair_arrive(f.next + 8 * (B_F1 - B_W1FULL - 1), peer);
  h_pack<NREG / 2>(p, d1, sc[2], sc[3]);
  h_store<NS, NS2>(p, hp);
  pinr<(NS2 > NREG / 2 ? NS2 : NREG / 2), NREG>(p);
  if (NS2 == NREG) warp_publish2(f.next + 8 * (B_HW + 1 - B_G2FULL));
  SCHED_BAR();
  mbar_finish(f.next, ok);
  f.next += 8;
}

struct G2 { uint32_t alo, blo, done, next; int aslot, bslot; };
template <bool FULL, bool RING, int LO, int STEP, int NP>
__device__ __forceinline__ void g2_stage(float (&d)[64], uint32_t sb, uint32_t peer, G2& g, uint32_t alo, int acc,
                                         const uint32_t (&p)[NP], uint32_t* hp, bool on) {
  const uint32_t bars = sb + SM_BAR;
  WG_FENCE();
  wgmma_ss<0, HI_SW128, 0, HI_A2, 1, 0>(d, alo, g.blo, acc);
  if (FULL) wgmma_ss<128, HI_SW128, 256, HI_A2, 1, 0>(d, alo, g.blo, 1);
  WG_COMMIT();
  const uint32_t next = min(g.next, BAR(B_G2FULL + 29));
  const uint32_t ok = mbar_probe(next);
  h_store<LO, LO + STEP>(p, hp, on);
  WG_WAIT(1);
  if (FULL) {
    wgmma_ss<256, HI_SW128, 512, HI_A2, 1, 0>(d, alo, g.blo, 1);
    wgmma_ss<384, HI_SW128, 768, HI_A2, 1, 0>(d, alo, g.blo, 1);
  } else {
    wgmma_ss<128, HI_SW128, 256, HI_A2, 1, 0>(d, alo, g.blo, 1);
  }
  WG_COMMIT();
  pair_arrive(g.done, peer);
  h_store<LO + STEP, LO + 2 * STEP>(p, hp, on);
  g.done = g.next + 8 * (B_F2 - B_G2FULL - 1);
  if (RING) { g.alo += g.aslot == 5 ? -5 * 512 : 512; g.aslot = g.aslot == 5 ? 0 : g.aslot + 1; }
  g.blo += g.bslot == 5 ? -5 * 1024 : 1024;
  g.bslot = g.bslot == 5 ? 0 : g.bslot + 1;
  TRD(64 + (g.next - BAR(B_G2FULL + 1)) / 8);
  mbar_finish(next, ok);
  g.next += 8;
  WG_WAIT(1);
}

template <int K0, int K1>
__device__ __forceinline__ void p_steps(float (&d)[48], uint32_t alo, uint32_t blo, int acc) {
  WG_FENCE();
  if (K0 <= 0 && K1 > 0) wgmma_ss<0, HI_SW128, 0, HI_SW64>(d, alo, blo, acc);
  if (K0 <= 1 && K1 > 1) wgmma_ss<2, HI_SW128, 64, HI_SW64>(d, alo, blo, 1);
  if (K0 <= 2 && K1 > 2) wgmma_ss<4, HI_SW128, 128, HI_SW64>(d, alo, blo, 1);
  if (K0 <= 3 && K1 > 3) wgmma_ss<6, HI_SW128, 192, HI_SW64>(d, alo, blo, 1);
  WG_COMMIT();
}
template <int H, int RH>
__device__ __forceinline__ void kv_pack(const float (&d)[48], uint32_t (&kv)[32]) {
#pragma unroll
  for (int i = 0; i < 4; i++) {
    const int j = 16 + 16 * (i >> 1) + 8 * (H & 1) + 4 * (i & 1) + 2 * RH;
    kv[8 * H + 4 * RH + i] = pack(d[j], d[j + 1]);
  }
}
template <int H, int RH>
__device__ __forceinline__ void kv_stg(const uint32_t (&kv)[32], uint32_t* gp) {
#pragma unroll
  for (int i = 0; i < 4; i++) gp[H * 2048 + RH * 128 + 32 * i] = kv[8 * H + 4 * RH + i];
}
__device__ __forceinline__ void q_pack(const float (&d)[48], uint32_t (&q0)[4], uint32_t (&q1)[4]) {
#pragma unroll
  for (int i = 0; i < 4; i++) {
    q0[i] = pack(d[2 * i] * QSCALE, d[2 * i + 1] * QSCALE);
    q1[i] = pack(d[8 + 2 * i] * QSCALE, d[9 + 2 * i] * QSCALE);
  }
}

__device__ __forceinline__ void mma16816(float& d0, float& d1, float& d2, float& d3, const uint32_t (&a)[4], uint32_t b0, uint32_t b1) {
  asm volatile("mma.sync.aligned.m16n8k16.row.col.f32.bf16.bf16.f32 {%0,%1,%2,%3}, {%4,%5,%6,%7}, {%8,%9}, {%0,%1,%2,%3};"
               : "+f"(d0), "+f"(d1), "+f"(d2), "+f"(d3) : "r"(a[0]), "r"(a[1]), "r"(a[2]), "r"(a[3]), "r"(b0), "r"(b1));
}
__device__ __forceinline__ uint32_t movm(uint32_t v) {
  uint32_t r; asm volatile("movmatrix.sync.aligned.m8n8.trans.b16 %0, %1;" : "=r"(r) : "r"(v)); return r;
}
__device__ __forceinline__ void attn_exact(float (&O)[8], float& l0, float& l1, const uint32_t (&q)[4], const uint32_t* kv,
                                           int rb, int row16, int lane) {
  float m0 = -INFINITY, m1 = -INFINITY;
  l0 = 0.f; l1 = 0.f;
#pragma unroll
  for (int i = 0; i < 8; i++) O[i] = 0.f;
  const int first = max(row16, 16 - 8 * rb);
  const int rr = (lane >> 2) - 2 * (lane & 3);
#pragma unroll 1
  for (int pass = 0; pass < 2; pass++) {
#pragma unroll 1
    for (int st = first; st <= row16 + 16; st++) {
      const uint32_t* a = kv + ((st >> 3) - 2) * 8 * 8192 + (st & 7) * 256;
      uint32_t k0 = __ldcg(a), k1 = __ldcg(a + 32), k2 = __ldcg(a + 128), k3 = __ldcg(a + 160);
      const uint32_t v0 = __ldcg(a + 64), v1 = __ldcg(a + 192), v2 = __ldcg(a + 96), v3 = __ldcg(a + 224);
      float s[8] = {0.f, 0.f, 0.f, 0.f, 0.f, 0.f, 0.f, 0.f};
      mma16816(s[0], s[1], s[2], s[3], q, k0, k1);
      mma16816(s[4], s[5], s[6], s[7], q, k2, k3);
      const int hi = st == row16 + 16 ? rr : 1000, lo = st == row16 ? rr : -1000;
#pragma unroll
      for (int i = 0; i < 8; i++) {
        const int c = 8 * (i >> 2) + (i & 1) - 4 * (i & 2);
        s[i] = (c <= hi && c > lo) ? s[i] : -INFINITY;
      }
      if (pass == 0) {
        m0 = fmaxf(fmaxf(m0, fmaxf(s[0], s[1])), fmaxf(s[4], s[5]));
        m1 = fmaxf(fmaxf(m1, fmaxf(s[2], s[3])), fmaxf(s[6], s[7]));
      } else {
#pragma unroll
        for (int i = 0; i < 8; i++) s[i] = ex2(s[i] - ((i & 2) ? m1 : m0));
        l0 += s[0] + s[1] + s[4] + s[5]; l1 += s[2] + s[3] + s[6] + s[7];
        const uint32_t p[4] = {pack(s[0], s[1]), pack(s[2], s[3]), pack(s[4], s[5]), pack(s[6], s[7])};
        k0 = movm(v0); k1 = movm(v1); k2 = movm(v2); k3 = movm(v3);
        mma16816(O[0], O[1], O[2], O[3], p, k0, k1);
        mma16816(O[4], O[5], O[6], O[7], p, k2, k3);
      }
    }
    m0 = quad_max(m0); m1 = quad_max(m1);
  }
  l0 = quad_sum(l0); l1 = quad_sum(l1);
}

#define OPQ(x) asm volatile("xor.b32 %0, %0, %1;" : "+r"(x) : "r"(a.zero))
struct Attn {
  float X[32], Y[32], Z[32], O[2][8];
  uint32_t P[32], PE[16], Q[4][4];
  float l0, l1, t0, t1, f0, f1, u0, u1, g0, g1, bias;
  int T, r0, lane, wq, zero;
  uint32_t ok, good, bad, mk[9], sb, aW, ob[4];
  uint4 kv;
  uint32_t* optr;
  char* gp;
};
template <int I> __device__ __forceinline__ void exp2x(float (&s)[32]) { s[I] = ex2(s[I]); s[I + 1] = ex2(s[I + 1]); pinr<I, I + 2>(s); }
template <int I> __device__ __forceinline__ void merge2(Attn& a) {
#pragma unroll
  for (int i = I; i < I + 2; i++) {
    asm("{.reg .pred p; setp.ge.s32 p, %2, %3; @p add.rn.f32 %0, %1, %4;}" : "+f"(a.X[i])
        : "f"(a.Y[i]), "r"(16 * (8 * (i >> 2) + (i & 1) - 4 * (i & 2))), "r"(a.r0), "f"(a.bias));
  }
  pinr<I, I + 2>(a.X);
}
template <int I, int T> __device__ __forceinline__ void trail2(Attn& a, const float (&s)[32]) {
  float& t = (I & 2) ? a.t1 : a.t0;
  float& l = (I & 2) ? a.l1 : a.l0;
  t = I < 4 ? s[I] + s[I + 1] : t + (s[I] + s[I + 1]);
  if (I >= 28) l = T == 0 ? t : a.T >= T ? l + t : l;
  if (I >= 28) asm volatile("" : "+f"(l)::"memory"); else asm volatile("" : "+f"(t)::"memory");
  constexpr int i = I / 2;
  const uint32_t p = pack(s[I], s[I + 1]);
  if (T == 0) {
    const uint32_t k = a.mk[(i >> 1) - (i & 1) + 1];
    a.P[i] = p & k;
    asm("mad.lo.s32 %0, %1, %2, %3;" : "=r"(a.PE[i]) : "r"(a.P[i]), "r"(a.zero - 1), "r"(p));
    pinr<i, i + 1>(a.PE);
  } else {
    a.P[16 * (T & 1) + i] = p;
  }
  pinr<16 * (T & 1) + i, 16 * (T & 1) + i + 1>(a.P);
}
template <int G, int J> __device__ __forceinline__ void attn_sub(Attn& a) {
  constexpr int T = (G / 4) % 4, I = 8 * (G % 4) + 2 * J;
  if constexpr (G < 64) {
    if constexpr (T == 0) {
      if constexpr (I == 0) merge2<0>(a);
      exp2x<I>(a.X);
      if constexpr (I + 2 < 32) merge2<I + 2>(a);
    } else if constexpr (T == 2) exp2x<I>(a.X);
    else exp2x<I>(a.Z);
  }
  if constexpr (G >= 1 && G < 65) {
    constexpr int T1 = ((G - 1) / 4) % 4, I1 = 8 * ((G - 1) % 4) + 2 * J;
    if constexpr (T1 & 1) trail2<I1, T1>(a, a.Z); else trail2<I1, T1>(a, a.X);
  }
}
template <int H> struct Off {
  static constexpr int D = sm_l(H) >> 4, E = sm_halo(H) >> 4, F3 = E + 256, F2 = E + 512;
};
template <int H> __device__ __forceinline__ uint32_t f1_base(const Attn& a) { return a.aW + ((a.T & 1) ? Off<H>::D - 256 : Off<H>::E + 768); }
template <int H> __device__ __forceinline__ void issue_de(Attn& a) {
  wgmma_qk<Off<H>::D>(a.X, a.Q[H], a.aW);
  wgmma_qk<Off<H>::E>(a.Y, a.Q[H], a.aW);
}
template <int C> __device__ __forceinline__ void issue_pv(Attn& a) {
  constexpr int H = C / 16, T = (C / 4) % 4, K = C % 4, p = 16 * (T & 1) + 4 * K;
  constexpr int off = (T == 0 ? Off<H>::D : T == 1 ? 0 : T == 2 ? Off<H>::F2 : Off<H>::F3) + 64 * K;
  wgmma_pv<off, (C % 16 != 0)>(a.O[H & 1], a.P[p], a.P[p + 1], a.P[p + 2], a.P[p + 3], T == 1 ? f1_base<H>(a) : a.aW);
  if constexpr (T == 0) wgmma_pv<Off<H>::E + 64 * K, 1>(a.O[H & 1], a.PE[p], a.PE[p + 1], a.PE[p + 2], a.PE[p + 3], a.aW);
}
template <int HF, int STEP> __device__ __forceinline__ void attn_finish(Attn& a) {
  const uint32_t sb = a.sb, bars = sb + SM_BAR;
  float (&O)[8] = a.O[HF & 1];
  if constexpr (STEP == 0) { a.u0 = __shfl_xor_sync(0xffffffffu, a.l0, 1); a.u1 = __shfl_xor_sync(0xffffffffu, a.l1, 1); }
  if constexpr (STEP == 1) {
    a.f0 = a.l0 + a.u0; a.f1 = a.l1 + a.u1;
    a.u0 = __shfl_xor_sync(0xffffffffu, a.f0, 2); a.u1 = __shfl_xor_sync(0xffffffffu, a.f1, 2);
  }
  if constexpr (STEP == 2) {
    a.f0 += a.u0; a.f1 += a.u1;
    asm("rcp.approx.ftz.f32 %0, %1;" : "=f"(a.u0) : "f"(a.f0));
    asm("rcp.approx.ftz.f32 %0, %1;" : "=f"(a.u1) : "f"(a.f1));
  }
  if constexpr (STEP == 3) { a.u0 *= a.g0; a.u1 *= a.g1; }
  if constexpr (STEP == 4) {
    pin(O);
    const float am = fmaxf(fmaxf(fmaxf(fabsf(O[0]), fabsf(O[1])), fmaxf(fabsf(O[2]), fabsf(O[3]))),
                           fmaxf(fmaxf(fabsf(O[4]), fabsf(O[5])), fmaxf(fabsf(O[6]), fabsf(O[7]))));
    a.good = __all_sync(0xffffffffu, a.f0 >= 0x1p-30f && a.f1 >= 0x1p-30f && a.f0 <= 0x1p60f && a.f1 <= 0x1p60f && am <= 0x1p120f);
  }
  if constexpr (STEP == 5) {
#pragma unroll
    for (int i = 0; i < 4; i++) { const float u = (i & 1) ? a.u1 : a.u0; a.ob[i] = pack(O[2 * i] * u, O[2 * i + 1] * u); }
    pin(a.ob);
  }
  if constexpr (STEP == 6) {
    uint32_t* op = a.optr + kg_o(HF) * 512;
    op[0] = a.ob[0]; op[32] = a.ob[1]; op[512] = a.ob[2]; op[544] = a.ob[3];
    a.bad |= a.good ? 0 : 1u << HF;
    __syncwarp();
    if (a.lane == 0 ? a.good : (HF == 0 && a.lane == 1)) mbar_arrive(a.lane ? BAR(B_SLOT) : BAR(B_HEAD + HF));
    TR(28 + 4 * (a.T & 1) + HF);
  }
  if constexpr (STEP < 4) asm volatile("" : "+f"(a.u0), "+f"(a.u1)::"memory");
}
template <int G> __device__ __forceinline__ void attn_region(Attn& a) {
  constexpr int H = G / 16, T = (G / 4) % 4, K = G % 4, G2 = G - 2, R = G % 16;
  const uint32_t sb = a.sb, bars = sb + SM_BAR;
  if constexpr (G >= 4 && !(G & 1)) { if constexpr (G <= 65) WG_WAIT(1); else WG_WAIT(0); }
  if constexpr (G < 64 && K == 0 && G > 0) {
    if constexpr (T == 0) { pin(a.X); pin(a.Y); OPQ(a.r0); } else if constexpr (T == 2) pin(a.X); else pin(a.Z);
  }
  if constexpr (G == 66) {
    attn_finish<3, 2>(a); attn_finish<3, 3>(a); attn_finish<3, 4>(a); attn_finish<3, 5>(a); attn_finish<3, 6>(a);
  } else {
    constexpr bool S = K == 1 && G > 1 && G < 61;
    if constexpr (H >= 1 && R >= 1 && R <= 3) attn_finish<H - 1, R - 1>(a);
    if constexpr (H >= 1 && R == 4) attn_finish<H - 1, 4>(a);
    if constexpr (H >= 1 && R == 5) attn_finish<H - 1, 6>(a);
    attn_sub<G, 0>(a); attn_sub<G, 1>(a);
    if constexpr (S && T == 3) mbar_finish(BAR(B_HALO + H + 1), a.ok); else SCHED_BAR();
    if constexpr (R == 12 && G < 60) a.ok = mbar_probe(BAR(B_HALO + H + 1));
    if constexpr (G2 >= 0 && (!PAIRS || (G & 1))) {
      WG_FENCE();
      if constexpr (PAIRS) issue_pv<G - 3>(a);
      issue_pv<G - 2>(a);
      if constexpr (S) {
        if constexpr (T == 0) wgmma_qk<0>(a.Z, a.Q[H], f1_base<H>(a));
        if constexpr (T == 1) wgmma_qk<Off<H>::F2>(a.X, a.Q[H], a.aW);
        if constexpr (T == 2) wgmma_qk<Off<H>::F3>(a.Z, a.Q[H], a.aW);
        if constexpr (T == 3) issue_de<H + 1>(a);
      }
      WG_COMMIT();
    }
    if constexpr (G < 8) {
      constexpr int o = (G >> 2) * 8192 + ((G >> 1) & 1) * 512;
      if constexpr (G & 1) *(uint4*)(a.gp + o) = a.kv; else a.kv = lds_v4(sb + sm_l(2) + o + (threadIdx.x >> 5) * 1024 + a.lane * 16);
    }
    if constexpr (G == 8) warp_publish(BAR(B_KVG + 2));
    if constexpr (G == 65) attn_finish<3, 1>(a);
    if constexpr (H >= 1 && R == 3) attn_finish<H - 1, 3>(a);
    if constexpr (H >= 1 && R == 4) attn_finish<H - 1, 5>(a);
    if constexpr (G == 14) {
      const uint32_t ga = sb + SM_G + (threadIdx.x >> 5) * 64 + (a.lane & 28);
      a.g0 = lds_f32(ga); a.g1 = lds_f32(ga + 32);
    }
    if constexpr (G == 12 && EARLYS) fence_async_smem();
    attn_sub<G, 2>(a); attn_sub<G, 3>(a);
    SCHED_BAR();
    attn_region<G + 1>(a);
  }
}

__global__ void __cluster_dims__(2, 1, 1) __launch_bounds__(512, 1)
fused_kernel(const char* __restrict__ x, const char* __restrict__ wqkv, Scratch* __restrict__ sc_,
             const char* __restrict__ gate_w, const char* __restrict__ wo, const char* __restrict__ w1,
             const char* __restrict__ w2, const __grid_constant__ Maps maps) {
  extern __shared__ __align__(1024) unsigned char smem[];
  const uint32_t sb = (uint32_t)__cvta_generic_to_shared(smem);
  const uint32_t bars = sb + SM_BAR;
  const int cl = blockIdx.x >> 1, rank = blockIdx.x & 1;
  const int cq = cl >= 36 ? ((cl - 36) * 37) >> 8 : 0;
  const int rb = 2 * (cl < 4 ? 0 : cl < 36 ? (cl - 4) & 7 : cl - 35 - 7 * cq) + rank;
  const int r = cl < 4 ? 4 + cl : cl < 36 ? (cl - 4) >> 3 : 4 + cq;
  const int bid = 8 * rb + r;
  const int cb = min(8 * NA + NB * r, 1312);
  if ((threadIdx.x >> 5) == 8) {
    if (elect()) {
#pragma unroll
      for (int j = 0; j < NEARLY; j++) mbar_init(BAR(B_XFULL + j), 1);
      asm volatile("fence.mbarrier_init.release.cluster;" ::: "memory");
#pragma unroll
      for (int j = 0; j < NEARLY; j++) {
        mbar_expect(BAR(B_XFULL + j), 16384 + 12288);
        tma2d(sb + SM_X + j * 16384, &maps.x, 64 * j, 128 * rb, BAR(B_XFULL + j));
        tma3d(sb + SM_U + j * 12288, &maps.wqkv, 64 * r, 64 * j, 0, BAR(B_XFULL + j));
      }
    }
    TR(54);
  }
  const int warp = __shfl_sync(0xffffffffu, threadIdx.x >> 5, 0);
  const int lane = threadIdx.x & 31;
  if (elect()) {
    if (warp >= NEARLY) mbar_init(BAR(warp), 1);
    mbar_init(BAR(B_AP + warp), 16);
    mbar_init(BAR(16 + warp), warp < 8 ? 8 : 1);
    asm volatile("fence.mbarrier_init.release.cluster;" ::: "memory");
    if (warp >= NEARLY) mbar_expect(BAR(warp), warp < 8 ? 16384 + 12288 : 12288);
    if (warp >= 12) mbar_expect(BAR(16 + warp), 16384);
  }
  __syncwarp();
  uint32_t peer;
  asm("mapa.shared::cluster.u32 %0, %1, %2;" : "=r"(peer) : "r"(sb), "r"(rank ^ 1));
  peer = lane == 0 ? 0 : lane == 1 ? peer - sb : (lane == 2 && warp >= 8) ? 8 * (B_GO - B_F1 - 10) : 0xffffffffu;

  if (warp >= 12) {
    if (warp == 14) TR(14);
    asm volatile("setmaxnreg.dec.sync.aligned.u32 24;");
    TR(44 + warp);
    cluster_sync();
    const char* p1 = rb >= 1 ? (const char*)sc_->kv + (size_t)(bid - 8) * 32768 : (const char*)sc_->zero;
    const char* p2 = rb >= 2 ? (const char*)sc_->kv + (size_t)(bid - 16) * 32768 : (const char*)sc_->zero;
    const int s1 = rb >= 1 ? 8192 : 0, s2 = rb >= 2 ? 8192 : 0;
    auto halo = [&](int h) {
      const uint32_t dst = sb + sm_halo(h);
      bulk_load(dst, p2 + h * s2, 8192, BAR(B_HALO + h));
      bulk_load(dst + 8192, p1 + h * s1, 8192, BAR(B_HALO + h));
    };
    if (warp == 12) {
      if (elect()) {
#pragma unroll 1
        for (int j = NEARLY + ((NEARLY ^ rank) & 1); j < 8; j += 2) {
          if (j >= NMID) mbar_wait(BAR(B_DUMMY));
          tma3d_mc(sb + SM_U + j * 12288, &maps.wqkv, 64 * r, 64 * j, 0, BAR(B_XFULL + j));
        }
#pragma unroll 1
        for (int i = rank; i < 8; i += 2) {
          const int j = !LAST4 || i < 4 ? i : i == 4 ? 7 : i - 1;
          mbar_wait(BAR(B_AP + (i < 5 ? i : i + 3)));
          tma3d_mc(sb + SM_U + (i < 5 ? i : i - 5) * 12288, &maps.wqkv, 64 * r + 32, 64 * j, 0, BAR(B_W2ND + j));
          if (i >= 2 && i < 5)
            asm volatile("cp.async.bulk.prefetch.tensor.3d.L2.global [%0, {%1, %2, 0}];" ::"l"(&maps.wqkv), "r"(64 * r + 32), "r"(64 * (i + 3 - LAST4)) : "memory");
        }
        mbar_wait(BAR(B_INIT));
#pragma unroll 1
        for (int n = rank; n < 8; n += 2) {
          mbar_wait(n < 4 ? BAR(B_AP + (LAST4 ? 11 + n : n ? 12 + n : 11)) : BAR(B_F1 + n - 4));
          tma3d_mc(sb + SM_W + ((n + 3) & 3) * 12288, &maps.w1s, NA * r, 64 * n, 0, BAR(B_W1FULL + n));
        }
#pragma unroll 1
        for (int n = rank; n < 8; n += 2) {
          mbar_wait(BAR(B_F1 + 4 + n - (XSLOT && n >= 5)));
          tma3d_mc(XSLOT && n == 5 ? sb + SM_X + 16384 : sb + SM_W + ((n + 3 - (XSLOT && n > 5)) & 3) * 12288, r < 7 ? &maps.w1s : &maps.w1a, r < 7 ? cb : 0, 64 * ((n + 1) & 7), r < 7 ? 0 : 41, BAR(B_W1FULL + 8 + n));
        }
        int slot = XSLOT ? 3 + rank : rank ? 0 : 5;
#pragma unroll 1
        for (int s = rank; s < 22; s += 2) {
          if (s == 4 - rank) { mbar_wait(BAR(B_F1 + H3AT)); mbar_wait(BAR(B_HALO + 2)); halo(3); }
          mbar_wait(s >= 6 ? BAR(B_F2 + (s < SA + 6 ? s - 6 : s - 4)) : BAR(B_F1 + (XSLOT ? (s < 3 ? 11 + (s > 0) : 14 + (s > 3)) : s == 0 ? 12 : 13 + (s >> 1))));
          tma2d_mc(sb + SM_W + slot * 8192, &maps.w2, 64 * r, 64 * s, BAR(B_G2FULL + (s < SA ? s : s + 2)));
          slot = slot >= 4 ? slot - 4 : slot + 2;
        }
      }
    } else if (warp == 13) {
      if (elect()) {
#pragma unroll 1
        for (int j = NEARLY; j < 8; j++) {
          if (j == NMID) mbar_wait_bounded(BAR(B_DUMMY));
          tma2d(sb + SM_X + j * 16384, &maps.x, 64 * j, 128 * rb, BAR(B_XFULL + j));
          if (j == NEARLY) TR(55);
        }
        mbar_wait_bounded(BAR(B_INIT));
        mbar_wait_bounded(BAR(B_F1 + X0AT));
        tma2d(sb + SM_X + 2 * 16384, &maps.x, 0, 128 * rb, BAR(B_W1FULL + 15));
        const char* src = (const char*)sc_->a2 + (size_t)rb * A2_BYTES;
        uint32_t dst = sb + SM_X + 3 * 16384;
#pragma unroll 1
        for (uint32_t full = BAR(B_G2FULL); full != BAR(B_G2FULL + 30); full += 8) {
          mbar_wait_bounded(full + 8 * (B_GO - B_G2FULL));
          bulk_load(dst, src, full == BAR(B_G2FULL + 23) ? 8192 : 16384, full);
          TRD(96 + (full - BAR(B_G2FULL)) / 8);
          src += 16384;
          dst = dst == sb + SM_X + 7 * 16384 ? sb + SM_X + 2 * 16384 : dst + 16384;
        }
#pragma unroll 1
        for (int s = 24; s < 30; s++) mbar_wait_bounded(BAR(B_G2FULL + s));
      }
    } else {
      if (warp == 14) mbar_wait(BAR(B_INIT));
      if (HELP1 && warp == 14) {
        mbar_wait(BAR(B_KVG));
        if (elect()) flag_add(sc_->kvflag + bid * 32);
        TR(46);
        mbar_wait(BAR(B_KVG + 1));
        uint4* dst = sc_->kv + (size_t)bid * 2048 + 512 + lane;
#pragma unroll 1
        for (int i = 0; i < 16; i += 4) {
          uint4 v[4];
#pragma unroll
          for (int k = 0; k < 4; k++) v[k] = lds_v4(sb + sm_l(1) + lane * 16 + (i + k) * 512);
#pragma unroll
          for (int k = 0; k < 4; k++) dst[(i + k) * 32] = v[k];
        }
        __syncwarp();
      }
      if (elect()) {
        const unsigned epoch = load_epoch(sc_);
        const unsigned* f1 = sc_->kvflag + (bid - (rb >= 1 ? 8 : 0)) * 32;
        const unsigned* f2 = sc_->kvflag + (bid - (rb >= 2 ? 16 : rb * 8)) * 32;
        unsigned* rdy = sc_->rdy + rb * 64 + r;
        if (warp == 14) {
#pragma unroll 1
          for (int i = HELP1; i < 3; i++) {
            mbar_wait(BAR(B_KVG + i));
            flag_add(sc_->kvflag + bid * 32);
            TR(46 + i);
          }
          flag_wait2(f1, f2, 3 * epoch + 3);
#pragma unroll
          for (int h = 0; h < 4; h++) {
            if (h == 0) { mbar_wait(BAR(B_SLOT)); halo(2); }
            mbar_wait(BAR(B_HEAD + h));
            if (h == 3) tma3d(sb + sm_wo(7), &maps.wo, 64 * r, 48, 4, BAR(B_G2FULL + 29));
            if (h == 0) mbar_wait(O0AT ? BAR(B_GO + O0AT - 1) : BAR(B_HAF));
            if (h == 0 || h == 3 || (h == 2 && !MERGE23)) flag_set(rdy + 8 * (h ? 2 + h : 1), epoch + 1);
            if (h == 3 && MERGE23) asm volatile("st.relaxed.gpu.global.u32 [%0], %1;" ::"l"(rdy + 32), "r"(epoch + 1) : "memory");
            if (h == 1 || h == 2) {
#pragma unroll
              for (int t = 4 * h - 4; t < 3 * h + 1; t++) {
                mbar_wait(BAR(B_F2 + (t < 4 ? WOAT + t : WOBT + t - 4)));
                tma3d(sb + sm_wo(t), &maps.wo, 64 * r, 8 * (t & 6), 4 * (t & 1), BAR(B_G2FULL + (t < 2 ? SA : 22) + t));
              }
            }
          }
          TR(50);
          if (PFOUT) asm volatile("prefetch.tensormap [%0];" ::"l"(&maps.out) : "memory");
          mbar_wait(BAR(B_F2));
          sc_->epoch[blockIdx.x] = epoch + 1;
        } else {
#pragma unroll 1
          for (int i = 2; i < 7; i++) asm volatile("prefetch.tensormap [%0];" ::"l"((const char*)&maps + i * 128) : "memory");
          auto pf2 = [&] { l2_prefetch(w2 + blockIdx.x * 11008, 11008); l2_prefetch(wo + blockIdx.x * 4096, 4096); };
          mbar_wait(BAR(B_INIT));
          mbar_wait(PF1AT < 8 ? BAR(B_XFULL + PF1AT) : BAR(B_AP + PF1AT - 8));
          l2_prefetch(w1 + blockIdx.x * 11008, 11008);
          if (PFAT < 8) { mbar_wait(BAR(B_AP + PFAT)); pf2(); }
          mbar_wait(BAR(B_KVG));
          if (rb >= 1) flag_wait2(f1, f2, 3 * epoch + 1);
          TR(49);
          halo(0);
          if (PFAT == 8) pf2();
          if (PFAT == 9) { mbar_wait(BAR(B_HALO)); pf2(); }
          mbar_wait(BAR(B_AP + 13));
          if (rb >= 1) flag_wait2(f1, f2, 3 * epoch + 2);
          TR(51);
          mbar_wait(BAR(B_F1 + HALO1));
          halo(1);
          if (PFAT >= 10) { mbar_wait(BAR(B_F1 + PFAT - 10)); pf2(); }
        }
      }
      if (warp == 15) {
        __syncwarp();
        const unsigned tag = load_epoch(sc_) + 1;
        unsigned* rdy = sc_->rdy + rb * 64;
        const int last = lane < SA ? (64 * lane + 63) / NA : lane < SA + 2 ? 11 + 4 * (lane - SA)
                       : lane < 24 ? 16 + (64 * (lane - SA - 2) + 63) / NB : (4 * lane - 69) & 31;
        const uint32_t need = (2u << last) - (1u << (last & 24));
        bool todo = lane < 30;
#pragma unroll 1
        for (int i = 0; i < 2; i++) {
          mbar_wait(BAR(B_HW + i));
          if (i) mbar_wait(BAR(B_HEAD + 1));
          if (elect()) {
            flag_set(rdy + 16 * i + r, tag);
            TR(52 + i);
            if (i) asm volatile("st.relaxed.gpu.global.u32 [%0], %1;" ::"l"(rdy + 24 + r), "r"(tag) : "memory");
          }
          __syncwarp();
          if (lane < 8 && !i) mbar_arrive(BAR(B_HAF));
          __syncwarp();
          auto look = [&](unsigned v0, unsigned v1) {
            const uint32_t m0 = __ballot_sync(0xffffffffu, v0 == tag), m1 = __ballot_sync(0xffffffffu, v1 == tag);
            if (todo && !(need & ~(lane < 26 ? m0 : m1))) {
              fence_async_global();
              mbar_arrive(BAR(B_GO + lane));
              todo = false;
            }
            __syncwarp();
          };
          unsigned it = 0, a0 = ld_flag(rdy + lane), a1 = ld_flag(rdy + 32 + lane);
          while (true) {
            look(a0, a1);
            if (!__any_sync(0xffffffffu, todo && (i || lane < SA + 2))) break;
            a0 = ld_flag(rdy + lane); a1 = ld_flag(rdy + 32 + lane);
            spin_guard(it);
          }
          TR(40 + 5 * i);
        }
      }
    }
  } else if (warp >= 8) {
    cluster_sync();
    asm volatile("setmaxnreg.inc.sync.aligned.u32 152;");
    const int wq = warp & 3;
    const unsigned epoch = load_epoch(sc_);
    {
      const int c = lane & 7, row = 16 * r + 4 * wq + (lane >> 3);
      uint4 wv[8];
#pragma unroll
      for (int j = 0; j < 8; j++) wv[j] = __ldg((const uint4*)gate_w + j * 8 + c);
      const uint32_t xa0 = sb + SM_X + row * 128 + ((c ^ (row & 7)) << 4);
      float z = 0.f;
      TR(7);
#pragma unroll 1
      for (int k = wq == 3 ? 9 : 2 + wq; k < 13; k += 4) {
        if (elect()) {
#pragma unroll
          for (int i = 0; i < 16; i++) mbar_init(BAR(16 * k + i), k < 5 ? 1 : k < 10 ? 8 : 5);
          asm volatile("fence.mbarrier_init.release.cluster;" ::: "memory");
        }
        __syncwarp();
      }
      if (wq < 3 && lane < 16) {
        const int i = B_W1FULL + 16 * wq + lane;
        mbar_expect(BAR(i), i == B_G2FULL + 23 ? 16384 : i >= B_G2FULL ? 24576 : i == B_W1FULL + 15 ? 12288 + 16384 : 12288);
      }
      __syncwarp();
      pair_arrive(BAR(B_INIT), lane == 2 ? 0xffffffffu : peer);
      TR(15);

            mbar_wait(BAR(B_AP + 1));
#pragma unroll 1
      for (int j = 2; j < 8; j++) mbar_wait(BAR(B_XFULL + j));
#pragma unroll
      for (int j = 0; j < 8; j++) {
        const uint4 xv = lds_v4(xa0 + j * 16384);
        const uint32_t xa[4] = {xv.x, xv.y, xv.z, xv.w}, wa[4] = {wv[j].x, wv[j].y, wv[j].z, wv[j].w};
#pragma unroll
        for (int e = 0; e < 4; e++) {
          z = fmaf(__uint_as_float(xa[e] << 16), __uint_as_float(wa[e] << 16), z);
          z = fmaf(__uint_as_float(xa[e] & 0xffff0000u), __uint_as_float(wa[e] & 0xffff0000u), z);
        }
      }
      z += __shfl_xor_sync(0xffffffffu, z, 1); z += __shfl_xor_sync(0xffffffffu, z, 2); z += __shfl_xor_sync(0xffffffffu, z, 4);
      const float g = 1.f / (1.f + __expf(-z));
      if (c == 0) asm volatile("st.relaxed.gpu.global.v2.b32 [%0], {%1, %2};" ::"l"(sc_->gate + 128 * rb + row), "f"(g), "r"(epoch + 1) : "memory");
    }
    TR(16);
    mbar_wait(BAR(B_INIT));
    mbar_wait(BAR(B_AP + 10));
    float sc[4];
    {
      const float gl = gate_of(sc_->gate + 128 * rb + (lane >> 4) * 64 + 16 * wq + (lane & 15), epoch);
      asm volatile("st.shared.f32 [%0], %1;" ::"r"(sb + SM_G + ((lane >> 4) * 64 + 16 * wq + (lane & 15)) * 4), "f"(gl) : "memory");
#pragma unroll
      for (int i = 0; i < 4; i++) sc[i] = 1.f - __shfl_sync(0xffffffffu, gl, (i >> 1) * 16 + (lane >> 2) + (i & 1) * 8);
    }
    mbar_wait(BAR(B_AP + FAT));
    TR(17);
    uint32_t* hp = (uint32_t*)((char*)sc_->a2 + (size_t)rb * A2_BYTES) + SA * r * 512 + wq * 64 + lane;
    const uint32_t none[1] = {0};
    F1 f = {dsc(sb + SM_X) + LO_X, dsc(sb + SM_W + 3 * 12288) + LO_W64, BAR(B_PRE), BAR(B_W1FULL + 1)};
    uint32_t pb[NB / 2];
    {
      uint32_t pa[NA / 2];
      float a0[NA / 2], a1[NA / 2], d0[NB / 2], d1[NB / 2];
      mbar_wait(BAR(B_W1FULL));
#pragma unroll 1
      for (int t = 0; t < 7; t++) { f1_block<1, 0>(a0, a1, f, peer, t > 0, 1024, (t & 3) == 0 ? -3 * 768 : 768, none, hp); TRD(160 + t);
        if (t == KVPAUSE) mbar_wait(BAR(B_KVW));
      }
      constexpr int XD = ((int)(SM_X + 16384) - (int)SM_W) / 16;
      constexpr int NT = (NA / 2 - NSA + 4 * TRA - 1) / (4 * TRA);
      f1_last<NSA, NSA, true>(a0, a1, f, peer, sc, pa, hp);
      f.alo -= 6 * 1024; f.blo += 768;
      WG_FENCE();
      wgmma_ss<0, HI_SW128, 0, HI_SW64>(d0, f.alo, f.blo, 0);
      wgmma_ss<2, HI_SW128, 64, HI_SW64>(d0, f.alo, f.blo, 1);
      wgmma_ss<4, HI_SW128, 128, HI_SW64>(d0, f.alo, f.blo, 1);
      wgmma_ss<6, HI_SW128, 192, HI_SW64>(d0, f.alo, f.blo, 1);
      WG_COMMIT();
      WG_WAIT(1);
      pin(a1);
      pair_arrive(BAR(B_F1 + 7), peer);
      h_pack<NA / 4>(pa, a1, sc[2], sc[3]);
      h_store<NSA, NSA + 2 * TRA>(pa, hp);
      pinr<NA / 4, NA / 2>(pa);
      TR(18);
      SCHED_BAR();
      WG_FENCE();
      wgmma_ss<512, HI_SW128, 0, HI_SW64>(d1, f.alo, f.blo, 0);
      wgmma_ss<514, HI_SW128, 64, HI_SW64>(d1, f.alo, f.blo, 1);
      WG_COMMIT();
      const uint32_t ok9 = mbar_probe(BAR(B_W1FULL + 9));
      h_store<NSA + 2 * TRA, NSA + 3 * TRA>(pa, hp);
      WG_WAIT(1);
      wgmma_ss<516, HI_SW128, 128, HI_SW64>(d1, f.alo, f.blo, 1);
      wgmma_ss<518, HI_SW128, 192, HI_SW64>(d1, f.alo, f.blo, 1);
      WG_COMMIT();
      h_store<NSA + 3 * TRA, NSA + 4 * TRA>(pa, hp);
      f.done = BAR(B_F1 + 8); f.next = BAR(B_W1FULL + 10);
      f.alo += 1024; f.blo -= 3 * 768;
      mbar_finish(BAR(B_W1FULL + 9), ok9);
      WG_WAIT(1);
      TRD(168);
      if (NT > 1) f1_block<NSA + 4 * TRA, TRA>(d0, d1, f, peer, 1, 1024, 768, pa, hp);
      if (NT > 2) f1_block<NSA + 8 * TRA, TRA>(d0, d1, f, peer, 1, 1024, 768, pa, hp);
      static_assert(NT <= 3, "");
      warp_publish2(BAR(B_HW));
      TR(19);
#pragma unroll 1
      for (int t = NT; t < 7; t++) { f1_block<1, 0>(d0, d1, f, peer, 1, t == 6 ? -5 * 1024 : 1024,
            !XSLOT ? (t == 4 ? -3 * 768 : 768) : t == 4 ? XD - 3 * 768 : t == 5 ? -XD : 768, none, hp); TRD(168 + t); }
      hp += (16 + (cb >> 3) - SA * r) * 512;
      f1_last<NSB, NSB2>(d0, d1, f, peer, sc, pb, hp);
      TR(20);
    }
    float d[64];
    G2 g2 = {dsc(sb + SM_W + (XSLOT ? 3 : 5) * 8192) + LO_W128, dsc(sb + SM_X + 3 * 16384) + LO_A2, BAR(B_PRE), BAR(B_G2FULL + 1), XSLOT ? 3 : 5, 1};
    constexpr int NG = (NB / 2 - NSB2 + 2 * TRB - 1) / (2 * TRB);
    static_assert(NG <= 4, "");
    TR(22);
    if (NG > 0) g2_stage<true, true, NSB2, TRB>(d, sb, peer, g2, g2.alo, 0, pb, hp, true);
    if (NG > 1) g2_stage<true, true, NSB2 + 2 * TRB, TRB>(d, sb, peer, g2, g2.alo, 1, pb, hp, true);
    if (NG > 2) g2_stage<true, true, NSB2 + 4 * TRB, TRB>(d, sb, peer, g2, g2.alo, 1, pb, hp, true);
    if (NG > 3) g2_stage<true, true, NSB2 + 6 * TRB, TRB>(d, sb, peer, g2, g2.alo, 1, pb, hp, true);
    if (NG > 0) warp_publish2(BAR(B_HW + 1));
    TR(21);
#pragma unroll 1
    for (int s = NG; s < SA; s++) g2_stage<true, true, 1, 0>(d, sb, peer, g2, g2.alo, NG || s, none, hp, false);
#pragma unroll
    for (int t = 0; t < 2; t++) g2_stage<true, false, 1, 0>(d, sb, peer, g2, dsc(sb + sm_wo(t)) + LO_W128, 1, none, hp, false);
#pragma unroll 1
    for (int s = SA + 2; s < 23; s++) {
      if (s == 19 && lane == 1) peer = 0xffffffffu;
      g2_stage<true, true, 1, 0>(d, sb, peer, g2, g2.alo, 1, none, hp, false);
    }
    g2_stage<false, true, 1, 0>(d, sb, peer, g2, g2.alo, 1, none, hp, false);
    TR(24);
#pragma unroll
    for (int t = 2; t < 8; t++)
      g2_stage<true, false, 1, 0>(d, sb, t == 2 ? peer : 0xffffffffu, g2, dsc(sb + sm_wo(t)) + LO_W128, 1, none, hp, false);
    WG_WAIT(0);
    pin(d);
    TR(26);
    {
      const uint32_t base = sb + SM_X + 16384 + ((lane >> 4) * 8 + (lane & 7)) * 128 + (((2 * wq + ((lane >> 3) & 1)) ^ (lane & 7)) << 4);
#pragma unroll
      for (int hf = 0; hf < TAILN; hf++) {
#pragma unroll
        for (int j = hf * (16 / TAILN); j < (hf + 1) * (16 / TAILN); j += 2)
          asm volatile("stmatrix.sync.aligned.m8n8.x4.trans.shared.b16 [%0], {%1, %2, %3, %4};"
                       ::"r"(base + j * 1024), "r"(pack(d[4 * j], d[4 * j + 1])), "r"(pack(d[4 * j + 2], d[4 * j + 3])),
                         "r"(pack(d[4 * j + 4], d[4 * j + 5])), "r"(pack(d[4 * j + 6], d[4 * j + 7])) : "memory");
        fence_async_smem();
        asm volatile("bar.sync 2, 128;" ::: "memory");
        if (wq == hf && elect())
          asm volatile("cp.async.bulk.tensor.2d.global.shared::cta.bulk_group [%0, {%2, %3}], [%1];\n cp.async.bulk.commit_group;"
                       ::"l"(&maps.out), "r"(sb + SM_X + 16384 + hf * (16384 / TAILN)), "r"(64 * r), "r"(128 * rb + hf * (128 / TAILN)) : "memory");
        __syncwarp();
      }
      asm volatile("cp.async.bulk.wait_group.read 0;" ::: "memory");
    }
    TR(27);
  } else {
    if (warp == 0) TR(8);
    asm volatile("setmaxnreg.inc.sync.aligned.u32 168;");
    if (warp == 0) TR(13);
    const int wg = warp >> 2, wq = warp & 3;
    Attn a;
    a.zero = blockIdx.y; a.bias = rb >= 2 ? 0.f : -INFINITY; a.bad = 0; a.T = 2 * rb + wg; a.lane = lane; a.wq = wq; a.sb = sb;
    a.r0 = 16 * (16 * wq + (lane >> 2) - 2 * (lane & 3) + 1);
    a.mk[0] = pmask<-8>(a.r0); a.mk[1] = pmask<0>(a.r0); a.mk[2] = pmask<8>(a.r0); a.mk[3] = pmask<16>(a.r0); a.mk[4] = pmask<24>(a.r0);
    a.mk[5] = pmask<32>(a.r0); a.mk[6] = pmask<40>(a.r0); a.mk[7] = pmask<48>(a.r0); a.mk[8] = pmask<56>(a.r0);
    pin(a.mk);
    a.aW = dsc(sb + wg * 4096);
    a.optr = (uint32_t*)((char*)sc_->a2 + (size_t)rb * A2_BYTES + 2 * r * 2048 + (8 * wg + 2 * wq) * 128) + lane;
    {
      float d1[48], d2[48];
      uint32_t alo = dsc(sb + SM_X + wg * 8192) + LO_X, blo = dsc(sb + SM_U) + LO_W64, done = BAR(B_ADUM);
      uint32_t* gp = (uint32_t*)sc_->kv + (size_t)bid * 8192 + (8 * wg + 2 * wq) * 128 + lane;
      uint32_t kv[32];
      if (warp == 0) TR(6);
      cluster_sync();
      if (warp == 0) TR(5);
      mbar_wait(BAR(B_XFULL));
      warp_arrive(BAR(B_DUMMY));
      TR(1 + 8 * wg);
#pragma unroll 1
      for (int j = 0; j < 8; j++) {
        if (wg == 0) TRD(208 + j);
        p_steps<0, 4>(d1, alo, blo, j > 0);
        alo += 1024; blo += 768;
        const uint32_t next = j < 7 ? BAR(B_XFULL + j + 1) : BAR(B_W2ND), okn = mbar_probe(next);
        WG_WAIT(1);
        pair_arrive(done, peer);
        done = BAR(B_AP + j);
        mbar_finish(next, okn);
      }
      alo -= 8 * 1024; blo -= 8 * 768;
      mbar_wait(BAR(B_INIT));
      if (wg == 0) TRD(216);
      p_steps<0, 4>(d2, alo, blo, 0);
      uint32_t ok = mbar_probe(BAR(B_W2ND + 1));
      WG_WAIT(1);
      pin(d1);
      pair_arrive(BAR(B_AP + 7), peer);
      TR(2 + 8 * wg);
      alo += 1024; blo += 768;
      kv_pack<0, 0>(d1, kv); kv_stg<0, 0>(kv, gp); kv_pack<0, 1>(d1, kv); kv_stg<0, 1>(kv, gp);
      warp_publish(BAR(B_KVG));
      mbar_finish(BAR(B_W2ND + 1), ok);
      p_steps<0, 4>(d2, alo, blo, 1);
      ok = mbar_probe(BAR(B_W2ND + 2));
      const uint32_t okl = mbar_probe(BAR(B_AP + 6));
      kv_pack<1, 0>(d1, kv); kv_pack<1, 1>(d1, kv);
      pinr<8, 16>(kv);
      WG_WAIT(1);
      pair_arrive(BAR(B_AP + 8), peer);
      mbar_finish(BAR(B_W2ND + 2), ok);
      const uint32_t addr = sb + (8 * wg + 2 * wq) * 512 + lane * 16;
      alo += 1024; blo += 768;
      p_steps<0, 4>(d2, alo, blo, 1);
      ok = mbar_probe(BAR(B_W2ND + 3));
      mbar_finish(BAR(B_AP + 6), okl);
#pragma unroll
      for (int i = 0; i < 4; i++) stsm4(addr + sm_l(i >> 1) + (i & 1) * 512, kv[4 * i], kv[4 * i + 1], kv[4 * i + 2], kv[4 * i + 3]);
      WG_WAIT(1);
      pair_arrive(BAR(B_AP + 9), peer);
      mbar_finish(BAR(B_W2ND + 3), ok);
      alo += 1024; blo += 768;
      if (wg == 0) TRD(219);
      p_steps<0, 4>(d2, alo, blo, 1);
      ok = mbar_probe(BAR(B_W2ND + 4));
      warp_publish(BAR(B_KVG + 1));
      q_pack(d1, a.Q[0], a.Q[1]);
      pin(a.Q[0]); pin(a.Q[1]);
      WG_WAIT(1);
      pair_arrive(BAR(B_AP + 10), peer);
      mbar_finish(BAR(B_W2ND + 4), ok);
#pragma unroll 1
      for (int j = 4; j < 8; j++) {
        alo += 1024; blo += LAST4 ? (j == 4 ? -3 * 768 : j == 7 ? 2 * 768 : 768) : j == 5 ? -4 * 768 : 768;
        if (wg == 0) TRD(216 + j);
        p_steps<0, 4>(d2, alo, blo, 1);
        if (EARLYS && j == 5) { fence_async_smem(); warp_publish(BAR(B_KVW)); }
        const uint32_t next = j < 7 ? BAR(B_W2ND + j + 1) : BAR(B_AP + 12), okn = mbar_probe(next);
        WG_WAIT(1);
        pair_arrive(BAR(B_AP + 7 + j), peer);
        mbar_finish(next, okn);
      }
      if (EARLYS) mbar_wait(BAR(B_KVW));
      ok = mbar_probe(BAR(B_HALO));
      WG_WAIT(0);
      pin(d2);
      pair_arrive(BAR(B_AP + 15), peer);
      kv_pack<2, 0>(d2, kv); kv_pack<2, 1>(d2, kv); kv_pack<3, 0>(d2, kv); kv_pack<3, 1>(d2, kv);
      if (LAST4) { pinr<16, 32>(kv); asm volatile("bar.sync 1, 256;" ::: "memory"); }
#pragma unroll
      for (int i = 4; i < 8; i++) stsm4(addr + sm_l(i >> 1) + (i & 1) * 512, kv[4 * i], kv[4 * i + 1], kv[4 * i + 2], kv[4 * i + 3]);
      q_pack(d2, a.Q[2], a.Q[3]);
      pin(a.Q[2]); pin(a.Q[3]);
      if (!EARLYS) { fence_async_smem(); warp_publish(BAR(B_KVW)); } else __syncwarp();
      TR(3 + 8 * wg);
      a.gp = (char*)(gp + 4096 + 3 * lane);
      if (EARLYS != 1) mbar_finish(BAR(B_HALO), ok);
      if (!EARLYS) mbar_wait(BAR(B_KVW));
      SCHED_BAR();
    }
    if (EARLYS != 1) TR(4 + 8 * wg);
    if (OFFS && wg) __nanosleep(OFFS);
    WG_FENCE();
    if (EARLYS != 1) { issue_de<0>(a); WG_COMMIT(); }
    wgmma_qk<0>(a.Z, a.Q[0], f1_base<0>(a));
    WG_COMMIT(); WG_WAIT(1);
    pin(a.X); pin(a.Y);
    attn_region<0>(a);
    if (a.bad) {
      unsigned it = 0;
      const unsigned target = 3 * load_epoch(sc_) + 3;
      while ((int)(ld_flag(sc_->kvflag + bid * 32) - target) < 0) spin_guard(it);
#pragma unroll 1
      for (int h = 0; h < 4; h++) {
        if (a.bad & (1u << h)) {
          float o[8], s0, s1;
          attn_exact(o, s0, s1, a.Q[0], (const uint32_t*)sc_->kv + (size_t)bid * 8192 + h * 2048 + lane, rb, 4 * wg + wq, lane);
          s0 = a.g0 / s0; s1 = a.g1 / s1;
          uint32_t* op = a.optr + kg_o(h) * 512;
          op[0] = pack(o[0] * s0, o[1] * s0); op[32] = pack(o[2] * s1, o[3] * s1);
          op[512] = pack(o[4] * s0, o[5] * s0); op[544] = pack(o[6] * s1, o[7] * s1);
          warp_publish(BAR(B_HEAD + h));
        }
#pragma unroll
        for (int i = 0; i < 4; i++) { a.Q[0][i] = a.Q[1][i]; a.Q[1][i] = a.Q[2][i]; a.Q[2][i] = a.Q[3][i]; }
      }
    }
  }
}

typedef CUresult (*EncodeFn)(CUtensorMap*, CUtensorMapDataType, cuuint32_t, void*, const cuuint64_t*, const cuuint64_t*,
                             const cuuint32_t*, const cuuint32_t*, CUtensorMapInterleave, CUtensorMapSwizzle,
                             CUtensorMapL2promotion, CUtensorMapFloatOOBfill);

void encode(EncodeFn fn, CUtensorMap* m, const void* p, int rank, cuuint64_t d0, cuuint64_t d1, cuuint64_t d2,
            cuuint64_t s1, cuuint64_t s2, cuuint32_t b0, cuuint32_t b1, cuuint32_t b2, CUtensorMapSwizzle sw,
            CUtensorMapL2promotion pr = CU_TENSOR_MAP_L2_PROMOTION_L2_128B) {
  const cuuint64_t gd[3] = {d0, d1, d2}, gs[2] = {s1, s2};
  const cuuint32_t bd[3] = {b0, b1, b2}, es[3] = {1, 1, 1};
  fn(m, CU_TENSOR_MAP_DATA_TYPE_BFLOAT16, rank, (void*)p, gd, gs, bd, es, CU_TENSOR_MAP_INTERLEAVE_NONE, sw,
     pr, CU_TENSOR_MAP_FLOAT_OOB_FILL_NONE);
}

}

extern "C" void kernel_launch(void* const* d_in, const int* in_sizes, int n_in, void* d_out, int out_size) {
  const char* x = (const char*)d_in[0];
  const char* wqkv = (const char*)d_in[1];
  const char* wo = (const char*)d_in[2];
  const char* w1 = (const char*)d_in[4];
  const char* w2 = (const char*)d_in[5];
  const char* gw = (const char*)d_in[6];
  void* fp = nullptr;
  cudaDriverEntryPointQueryResult q;
  cudaGetDriverEntryPoint("cuTensorMapEncodeTiled", &fp, cudaEnableDefault, &q);
  EncodeFn fn = (EncodeFn)fp;
  void* sc = nullptr;
  cudaGetSymbolAddress(&sc, g_scratch);
  Maps m;
  const CUtensorMapSwizzle S128 = CU_TENSOR_MAP_SWIZZLE_128B, S64 = CU_TENSOR_MAP_SWIZZLE_64B;
  encode(fn, &m.x, x, 2, D_, S_, 1, D_ * 2, 0, 64, 128, 1, S128);
  encode(fn, &m.wqkv, wqkv, 3, D_, D_, 3, 3 * D_ * 2, D_ * 2, 32, 64, 3, S64, QPROM);
  encode(fn, &m.w1a, w1, 3, 32, D_, 43, DFF * 2, 64, 32, 64, 3, S64);
  encode(fn, &m.w1s, w1, 3, DFF - 64, D_, 3, DFF * 2, 64, 32, 64, 3, S64);
  encode(fn, &m.w2, w2, 2, D_, DFF, 1, D_ * 2, 0, 64, 64, 1, S128);
  encode(fn, &m.wo, wo, 3, D_, 64, 8, D_ * 2, 64 * D_ * 2, 64, 16, 4, S128);
  encode(fn, &m.out, d_out, 2, D_, S_, 1, D_ * 2, 0, 64, 128 / TAILN, 1, S128);
  cudaFuncSetAttribute(fused_kernel, cudaFuncAttributeMaxDynamicSharedMemorySize, SM_TOTAL);
  fused_kernel<<<128, 512, SM_TOTAL>>>(x, wqkv, (Scratch*)sc, gw, wo, w1, w2, m);
}
```
